```python
import torch

def _softmax(x, axis=-1):
    return torch.softmax(x, dim=axis)
def _gelu(x):
    return torch.nn.functional.gelu(x, approximate="tanh")
def _silu(x):
    return torch.nn.functional.silu(x)
def _sigmoid(x):
    return torch.sigmoid(x)
def _layernorm(x, axis=-1, eps=1e-5):
    m = x.mean(dim=axis, keepdim=True)
    v = x.var(dim=axis, keepdim=True, unbiased=False)
    return (x - m) / torch.sqrt(v + eps)
def _scatter_add(tgt, idx, src, axis=0):
    return tgt.clone().index_add_(axis, idx, src)
def _segment_sum(src, seg, n):
    out = torch.zeros((n,) + src.shape[1:], dtype=src.dtype)
    return out.index_add_(0, seg, src)
def _pad(x, pw):
    flat = tuple(v for pair in reversed(pw) for v in pair)
    return torch.nn.functional.pad(x, flat)

kernel_name = 'interleave_layers__sliding_block__mixer_channel_mlp__prompt'

def setup_inputs():

    _w = (lambda a: (lambda t: t.to(torch.bfloat16) if t.is_floating_point() else t)(torch.as_tensor(a)))
    def _A_setup():
        B, S, D = 1, 2048, 640
        return {
            "x": _w((lambda *s: torch.randn(*s, dtype=torch.bfloat16) * 0.05)(B, S, D)),
            "wqkv": _w((lambda *s: torch.randn(*s, dtype=torch.bfloat16) * 0.05)(D, 3 * D)),
            "wo": _w((lambda *s: torch.randn(*s, dtype=torch.bfloat16) * 0.05)(D, D)),
        }
    _A_in = _A_setup()

    def _B_setup():
        B, S, D, F = 1, 2048, 640, 1728
        return {
            "x": _w((lambda *s: torch.randn(*s, dtype=torch.bfloat16) * 0.05)(B, S, D)),
            "w1": _w((lambda *s: torch.randn(*s, dtype=torch.bfloat16) * 1.6)(D, F) * (D ** -0.5)),
            "b1": _w((lambda *s: torch.randn(*s, dtype=torch.bfloat16) * 1.6)(F)),
            "w2": _w((lambda *s: torch.randn(*s, dtype=torch.bfloat16) * 0.4)(F, D) * (F ** -0.5)),
            "b2": _w((lambda *s: torch.randn(*s, dtype=torch.bfloat16) * 0.4)(D)),
        }
    _B_in = _B_setup()

    return {
        "A_x": _A_in["x"],
        "A_wqkv": _A_in["wqkv"],
        "A_wo": _A_in["wo"],
        "B_x": _B_in["x"],
        "B_w1": _B_in["w1"],
        "B_b1": _B_in["b1"],
        "B_w2": _B_in["w2"],
        "B_b2": _B_in["b2"],
    }

def reference(A_x, A_wqkv, A_wo, B_x, B_w1, B_b1, B_w2, B_b2):
    def _A_ref(x, wqkv, wo):
        B, S, D = x.shape
        H = 32; Dh = D // H; W = 256
        qkv = (lambda x, *d: x.permute(*d))((x @ wqkv).reshape(B, S, 3, H, Dh), 2, 0, 3, 1, 4)
        q, k, v = qkv[0], qkv[1], qkv[2]
        scores = torch.einsum("bhqd,bhkd->bhqk", q, k) * (Dh ** -0.5)
        idx = torch.arange(S)
        mask = (idx[:, None] - idx[None, :] >= 0) & (idx[:, None] - idx[None, :] < W)
        scores = torch.where(mask[None, None], scores, -1e9)
        p = _softmax(scores, axis=-1)
        o = torch.einsum("bhqk,bhkd->bhqd", p, v)
        return (lambda x, *d: x.permute(*d))(o, 0, 2, 1, 3).reshape(B, S, D) @ wo

    def _B_ref(x, w1, b1, w2, b2):
        y = _layernorm(x, axis=-1)
        h = _gelu(torch.einsum("bsd,df->bsf", y, w1) + b1)
        return torch.einsum("bsf,fd->bsd", h, w2) + b2

    x = A_x
    x = x + _A_ref(_layernorm(x, axis=-1), A_wqkv, A_wo)
    x = x + _B_ref(_layernorm(x, axis=-1), B_w1, B_b1, B_w2, B_b2)
    x = x + _A_ref(_layernorm(x, axis=-1), A_wqkv, A_wo)
    x = x + _B_ref(_layernorm(x, axis=-1), B_w1, B_b1, B_w2, B_b2)
    return x
```

```cpp
#include <cuda_runtime.h>
#include <cuda_bf16.h>
#include <cuda.h>
#include <stdint.h>
#include <type_traits>

namespace {

typedef __nv_bfloat16 bf16;

constexpr int NPH = 4;
constexpr int S_ = 2048, D_ = 640, F_ = 1728;
constexpr int UNIT = 15360, NU = 8, ASLOT = 10240, NA = 5;
constexpr int SM_A = NU * UNIT;
constexpr int SM_BAR = SM_A + 2 * NA * ASLOT;
constexpr int B_WFULL = SM_BAR, B_EP = B_WFULL + 64, B_PLD = B_EP + 8;
constexpr int B_AFULL = SM_BAR + 80;
constexpr int B_AEMPTY = SM_BAR + 160, B_STAGED = SM_BAR + 240, B_ST = B_STAGED + 64;
constexpr int B_WEMPTY = SM_BAR + 320;
constexpr int B_KVFREE = SM_BAR + 400, B_PREP = B_KVFREE + 16, B_HL = B_PREP + 8, B_GO = B_HL + 8;
constexpr int B_CSQ = SM_BAR + 440, B_LATE = B_CSQ + 16, B_CSP = B_LATE + 8;
constexpr int SM_EPOCH = SM_BAR + 480;
constexpr int SM_CSQ = SM_BAR + 512;
constexpr int SM_CB1 = SM_CSQ + 960;
constexpr int SM_B2 = SM_CB1 + 1792;
constexpr int SM_ZERO = SM_B2 + 320;
constexpr int SM_LN = SM_ZERO + 320;
constexpr int SM_END = SM_LN + 1024;
constexpr int SMEM_BYTES = SM_END + 1024;

constexpr int FL_KV = 0  , FL_O = 32  , FL_X = 36  , FL_H = 40  , FL_S0 = 44;
constexpr int FL_CS = 36 * 64;

struct Maps { CUtensorMap x0, x16, xr, q64, q16, wo, out, w1i, w2i; };
struct Params { const bf16 *x, *wqkv, *wo, *w1, *b1, *w2, *b2; };

constexpr int G_O = 0, G_X1 = 32 * 80 * 1024, G_X2 = 2 * G_X1, G_H = 3 * G_X1, G_KV = G_H + 32 * 216 * 1024;
__device__ __align__(1024) unsigned char g_act[G_KV + 2 * 8 * 2 * 327680];
#define g_o (g_act + G_O)
#define g_x1 (g_act + G_X1)
#define g_x2 (g_act + G_X2)
#define g_h (g_act + G_H)
#define g_kv (g_act + G_KV)
constexpr int IMG_Q = 0, IMG_1 = 40 * 7680, IMG_2 = IMG_1 + 40 * 7168, IMG_BYTES = IMG_2 + 109 * 2560;
__device__ __align__(1024) unsigned char g_img[8 * IMG_BYTES];
__device__ __align__(1024) float g_cs[2 * 16 * 8 * 240];
__device__ __align__(1024) float2 g_st[4 * 32 * 64 * 8];
__device__ __align__(1024) unsigned g_flags[36 * 64 + 64];
__device__ unsigned g_ticket;

__device__ __forceinline__ void wgmma_n192(float (&d)[96], uint64_t da, uint64_t db) {
  asm volatile(
      "wgmma.mma_async.sync.aligned.m64n192k16.f32.bf16.bf16 {"
      "%0, %1, %2, %3, %4, %5, %6, %7, %8, %9, %10, %11, %12, %13, %14, %15, %16, %17, %18, %19, %20, %21, %22, %23, %24, %25, %26, %27, %28, %29, %30, %31, "
      "%32, %33, %34, %35, %36, %37, %38, %39, %40, %41, %42, %43, %44, %45, %46, %47, %48, %49, %50, %51, %52, %53, %54, %55, %56, %57, %58, %59, %60, %61, "
      "%62, %63, %64, %65, %66, %67, %68, %69, %70, %71, %72, %73, %74, %75, %76, %77, %78, %79, %80, %81, %82, %83, %84, %85, %86, %87, %88, %89, %90, %91, "
      "%92, %93, %94, %95"
      "}, %96, %97, 1, 1, 1, 0, 1;"
    : "+f"(d[0]), "+f"(d[1]), "+f"(d[2]), "+f"(d[3]), "+f"(d[4]), "+f"(d[5]), "+f"(d[6]), "+f"(d[7]), "+f"(d[8]), "+f"(d[9]), "+f"(d[10]), "+f"(d[11]),
      "+f"(d[12]), "+f"(d[13]), "+f"(d[14]), "+f"(d[15]), "+f"(d[16]), "+f"(d[17]), "+f"(d[18]), "+f"(d[19]), "+f"(d[20]), "+f"(d[21]), "+f"(d[22]),
      "+f"(d[23]), "+f"(d[24]), "+f"(d[25]), "+f"(d[26]), "+f"(d[27]), "+f"(d[28]), "+f"(d[29]), "+f"(d[30]), "+f"(d[31]), "+f"(d[32]), "+f"(d[33]),
      "+f"(d[34]), "+f"(d[35]), "+f"(d[36]), "+f"(d[37]), "+f"(d[38]), "+f"(d[39]), "+f"(d[40]), "+f"(d[41]), "+f"(d[42]), "+f"(d[43]), "+f"(d[44]),
      "+f"(d[45]), "+f"(d[46]), "+f"(d[47]), "+f"(d[48]), "+f"(d[49]), "+f"(d[50]), "+f"(d[51]), "+f"(d[52]), "+f"(d[53]), "+f"(d[54]), "+f"(d[55]),
      "+f"(d[56]), "+f"(d[57]), "+f"(d[58]), "+f"(d[59]), "+f"(d[60]), "+f"(d[61]), "+f"(d[62]), "+f"(d[63]), "+f"(d[64]), "+f"(d[65]), "+f"(d[66]),
      "+f"(d[67]), "+f"(d[68]), "+f"(d[69]), "+f"(d[70]), "+f"(d[71]), "+f"(d[72]), "+f"(d[73]), "+f"(d[74]), "+f"(d[75]), "+f"(d[76]), "+f"(d[77]),
      "+f"(d[78]), "+f"(d[79]), "+f"(d[80]), "+f"(d[81]), "+f"(d[82]), "+f"(d[83]), "+f"(d[84]), "+f"(d[85]), "+f"(d[86]), "+f"(d[87]), "+f"(d[88]),
      "+f"(d[89]), "+f"(d[90]), "+f"(d[91]), "+f"(d[92]), "+f"(d[93]), "+f"(d[94]), "+f"(d[95])
    : "l"(da), "l"(db));
}
__device__ __forceinline__ void wgmma_n48(float (&d)[24], uint64_t da, uint64_t db) {
  asm volatile(
      "wgmma.mma_async.sync.aligned.m64n48k16.f32.bf16.bf16 {"
      "%0, %1, %2, %3, %4, %5, %6, %7, %8, %9, %10, %11, %12, %13, %14, %15, %16, %17, %18, %19, %20, %21, %22, %23"
      "}, %24, %25, 1, 1, 1, 0, 1;"
    : "+f"(d[0]), "+f"(d[1]), "+f"(d[2]), "+f"(d[3]), "+f"(d[4]), "+f"(d[5]), "+f"(d[6]), "+f"(d[7]), "+f"(d[8]), "+f"(d[9]), "+f"(d[10]), "+f"(d[11]),
      "+f"(d[12]), "+f"(d[13]), "+f"(d[14]), "+f"(d[15]), "+f"(d[16]), "+f"(d[17]), "+f"(d[18]), "+f"(d[19]), "+f"(d[20]), "+f"(d[21]), "+f"(d[22]),
      "+f"(d[23])
    : "l"(da), "l"(db));
}
__device__ __forceinline__ void wgmma_n80(float (&d)[40], uint64_t da, uint64_t db) {
  asm volatile(
      "wgmma.mma_async.sync.aligned.m64n80k16.f32.bf16.bf16 {"
      "%0, %1, %2, %3, %4, %5, %6, %7, %8, %9, %10, %11, %12, %13, %14, %15, %16, %17, %18, %19, %20, %21, %22, %23, %24, %25, %26, %27, %28, %29, %30, %31, "
      "%32, %33, %34, %35, %36, %37, %38, %39"
      "}, %40, %41, 1, 1, 1, 0, 1;"
    : "+f"(d[0]), "+f"(d[1]), "+f"(d[2]), "+f"(d[3]), "+f"(d[4]), "+f"(d[5]), "+f"(d[6]), "+f"(d[7]), "+f"(d[8]), "+f"(d[9]), "+f"(d[10]), "+f"(d[11]),
      "+f"(d[12]), "+f"(d[13]), "+f"(d[14]), "+f"(d[15]), "+f"(d[16]), "+f"(d[17]), "+f"(d[18]), "+f"(d[19]), "+f"(d[20]), "+f"(d[21]), "+f"(d[22]),
      "+f"(d[23]), "+f"(d[24]), "+f"(d[25]), "+f"(d[26]), "+f"(d[27]), "+f"(d[28]), "+f"(d[29]), "+f"(d[30]), "+f"(d[31]), "+f"(d[32]), "+f"(d[33]),
      "+f"(d[34]), "+f"(d[35]), "+f"(d[36]), "+f"(d[37]), "+f"(d[38]), "+f"(d[39])
    : "l"(da), "l"(db));
}
__device__ __forceinline__ void wgmma_n224(float (&d)[112], uint64_t da, uint64_t db) {
  asm volatile(
      "wgmma.mma_async.sync.aligned.m64n224k16.f32.bf16.bf16 {"
      "%0, %1, %2, %3, %4, %5, %6, %7, %8, %9, %10, %11, %12, %13, %14, %15, %16, %17, %18, %19, %20, %21, %22, %23, %24, %25, %26, %27, %28, %29, %30, %31, "
      "%32, %33, %34, %35, %36, %37, %38, %39, %40, %41, %42, %43, %44, %45, %46, %47, %48, %49, %50, %51, %52, %53, %54, %55, %56, %57, %58, %59, %60, %61, "
      "%62, %63, %64, %65, %66, %67, %68, %69, %70, %71, %72, %73, %74, %75, %76, %77, %78, %79, %80, %81, %82, %83, %84, %85, %86, %87, %88, %89, %90, %91, "
      "%92, %93, %94, %95, %96, %97, %98, %99, %100, %101, %102, %103, %104, %105, %106, %107, %108, %109, %110, %111"
      "}, %112, %113, 1, 1, 1, 0, 1;"
    : "+f"(d[0]), "+f"(d[1]), "+f"(d[2]), "+f"(d[3]), "+f"(d[4]), "+f"(d[5]), "+f"(d[6]), "+f"(d[7]), "+f"(d[8]), "+f"(d[9]), "+f"(d[10]), "+f"(d[11]),
      "+f"(d[12]), "+f"(d[13]), "+f"(d[14]), "+f"(d[15]), "+f"(d[16]), "+f"(d[17]), "+f"(d[18]), "+f"(d[19]), "+f"(d[20]), "+f"(d[21]), "+f"(d[22]),
      "+f"(d[23]), "+f"(d[24]), "+f"(d[25]), "+f"(d[26]), "+f"(d[27]), "+f"(d[28]), "+f"(d[29]), "+f"(d[30]), "+f"(d[31]), "+f"(d[32]), "+f"(d[33]),
      "+f"(d[34]), "+f"(d[35]), "+f"(d[36]), "+f"(d[37]), "+f"(d[38]), "+f"(d[39]), "+f"(d[40]), "+f"(d[41]), "+f"(d[42]), "+f"(d[43]), "+f"(d[44]),
      "+f"(d[45]), "+f"(d[46]), "+f"(d[47]), "+f"(d[48]), "+f"(d[49]), "+f"(d[50]), "+f"(d[51]), "+f"(d[52]), "+f"(d[53]), "+f"(d[54]), "+f"(d[55]),
      "+f"(d[56]), "+f"(d[57]), "+f"(d[58]), "+f"(d[59]), "+f"(d[60]), "+f"(d[61]), "+f"(d[62]), "+f"(d[63]), "+f"(d[64]), "+f"(d[65]), "+f"(d[66]),
      "+f"(d[67]), "+f"(d[68]), "+f"(d[69]), "+f"(d[70]), "+f"(d[71]), "+f"(d[72]), "+f"(d[73]), "+f"(d[74]), "+f"(d[75]), "+f"(d[76]), "+f"(d[77]),
      "+f"(d[78]), "+f"(d[79]), "+f"(d[80]), "+f"(d[81]), "+f"(d[82]), "+f"(d[83]), "+f"(d[84]), "+f"(d[85]), "+f"(d[86]), "+f"(d[87]), "+f"(d[88]),
      "+f"(d[89]), "+f"(d[90]), "+f"(d[91]), "+f"(d[92]), "+f"(d[93]), "+f"(d[94]), "+f"(d[95]), "+f"(d[96]), "+f"(d[97]), "+f"(d[98]), "+f"(d[99]),
      "+f"(d[100]), "+f"(d[101]), "+f"(d[102]), "+f"(d[103]), "+f"(d[104]), "+f"(d[105]), "+f"(d[106]), "+f"(d[107]), "+f"(d[108]), "+f"(d[109]),
      "+f"(d[110]), "+f"(d[111])
    : "l"(da), "l"(db));
}
__device__ __forceinline__ void wgmma_rs160_init(float* d, uint32_t a0, uint32_t a1, uint32_t a2, uint32_t a3, uint64_t db) {
  asm volatile(
      "wgmma.mma_async.sync.aligned.m64n160k16.f32.bf16.bf16 {"
      "%0, %1, %2, %3, %4, %5, %6, %7, %8, %9, %10, %11, %12, %13, %14, %15, %16, %17, %18, %19, %20, %21, %22, %23, %24, %25, %26, %27, %28, %29, %30, %31, "
      "%32, %33, %34, %35, %36, %37, %38, %39, %40, %41, %42, %43, %44, %45, %46, %47, %48, %49, %50, %51, %52, %53, %54, %55, %56, %57, %58, %59, %60, %61, "
      "%62, %63, %64, %65, %66, %67, %68, %69, %70, %71, %72, %73, %74, %75, %76, %77, %78, %79"
      "}, {%80, %81, %82, %83}, %84, 0, 1, 1, 0;"
    : "=f"(d[0]), "=f"(d[1]), "=f"(d[2]), "=f"(d[3]), "=f"(d[4]), "=f"(d[5]), "=f"(d[6]), "=f"(d[7]), "=f"(d[8]), "=f"(d[9]), "=f"(d[10]), "=f"(d[11]),
      "=f"(d[12]), "=f"(d[13]), "=f"(d[14]), "=f"(d[15]), "=f"(d[16]), "=f"(d[17]), "=f"(d[18]), "=f"(d[19]), "=f"(d[20]), "=f"(d[21]), "=f"(d[22]),
      "=f"(d[23]), "=f"(d[24]), "=f"(d[25]), "=f"(d[26]), "=f"(d[27]), "=f"(d[28]), "=f"(d[29]), "=f"(d[30]), "=f"(d[31]), "=f"(d[32]), "=f"(d[33]),
      "=f"(d[34]), "=f"(d[35]), "=f"(d[36]), "=f"(d[37]), "=f"(d[38]), "=f"(d[39]), "=f"(d[40]), "=f"(d[41]), "=f"(d[42]), "=f"(d[43]), "=f"(d[44]),
      "=f"(d[45]), "=f"(d[46]), "=f"(d[47]), "=f"(d[48]), "=f"(d[49]), "=f"(d[50]), "=f"(d[51]), "=f"(d[52]), "=f"(d[53]), "=f"(d[54]), "=f"(d[55]),
      "=f"(d[56]), "=f"(d[57]), "=f"(d[58]), "=f"(d[59]), "=f"(d[60]), "=f"(d[61]), "=f"(d[62]), "=f"(d[63]), "=f"(d[64]), "=f"(d[65]), "=f"(d[66]),
      "=f"(d[67]), "=f"(d[68]), "=f"(d[69]), "=f"(d[70]), "=f"(d[71]), "=f"(d[72]), "=f"(d[73]), "=f"(d[74]), "=f"(d[75]), "=f"(d[76]), "=f"(d[77]),
      "=f"(d[78]), "=f"(d[79])
    : "r"(a0), "r"(a1), "r"(a2), "r"(a3), "l"(db));
}
__device__ __forceinline__ void wgmma_rs160(float* d, uint32_t a0, uint32_t a1, uint32_t a2, uint32_t a3, uint64_t db) {
  asm volatile(
      "wgmma.mma_async.sync.aligned.m64n160k16.f32.bf16.bf16 {"
      "%0, %1, %2, %3, %4, %5, %6, %7, %8, %9, %10, %11, %12, %13, %14, %15, %16, %17, %18, %19, %20, %21, %22, %23, %24, %25, %26, %27, %28, %29, %30, %31, "
      "%32, %33, %34, %35, %36, %37, %38, %39, %40, %41, %42, %43, %44, %45, %46, %47, %48, %49, %50, %51, %52, %53, %54, %55, %56, %57, %58, %59, %60, %61, "
      "%62, %63, %64, %65, %66, %67, %68, %69, %70, %71, %72, %73, %74, %75, %76, %77, %78, %79"
      "}, {%80, %81, %82, %83}, %84, 1, 1, 1, 0;"
    : "+f"(d[0]), "+f"(d[1]), "+f"(d[2]), "+f"(d[3]), "+f"(d[4]), "+f"(d[5]), "+f"(d[6]), "+f"(d[7]), "+f"(d[8]), "+f"(d[9]), "+f"(d[10]), "+f"(d[11]),
      "+f"(d[12]), "+f"(d[13]), "+f"(d[14]), "+f"(d[15]), "+f"(d[16]), "+f"(d[17]), "+f"(d[18]), "+f"(d[19]), "+f"(d[20]), "+f"(d[21]), "+f"(d[22]),
      "+f"(d[23]), "+f"(d[24]), "+f"(d[25]), "+f"(d[26]), "+f"(d[27]), "+f"(d[28]), "+f"(d[29]), "+f"(d[30]), "+f"(d[31]), "+f"(d[32]), "+f"(d[33]),
      "+f"(d[34]), "+f"(d[35]), "+f"(d[36]), "+f"(d[37]), "+f"(d[38]), "+f"(d[39]), "+f"(d[40]), "+f"(d[41]), "+f"(d[42]), "+f"(d[43]), "+f"(d[44]),
      "+f"(d[45]), "+f"(d[46]), "+f"(d[47]), "+f"(d[48]), "+f"(d[49]), "+f"(d[50]), "+f"(d[51]), "+f"(d[52]), "+f"(d[53]), "+f"(d[54]), "+f"(d[55]),
      "+f"(d[56]), "+f"(d[57]), "+f"(d[58]), "+f"(d[59]), "+f"(d[60]), "+f"(d[61]), "+f"(d[62]), "+f"(d[63]), "+f"(d[64]), "+f"(d[65]), "+f"(d[66]),
      "+f"(d[67]), "+f"(d[68]), "+f"(d[69]), "+f"(d[70]), "+f"(d[71]), "+f"(d[72]), "+f"(d[73]), "+f"(d[74]), "+f"(d[75]), "+f"(d[76]), "+f"(d[77]),
      "+f"(d[78]), "+f"(d[79])
    : "r"(a0), "r"(a1), "r"(a2), "r"(a3), "l"(db));
}
__device__ __forceinline__ void wgmma_rs24_init(float* d, uint32_t a0, uint32_t a1, uint32_t a2, uint32_t a3, uint64_t db) {
  asm volatile(
      "wgmma.mma_async.sync.aligned.m64n24k16.f32.bf16.bf16 {"
      "%0, %1, %2, %3, %4, %5, %6, %7, %8, %9, %10, %11"
      "}, {%12, %13, %14, %15}, %16, 0, 1, 1, 1;"
    : "=f"(d[0]), "=f"(d[1]), "=f"(d[2]), "=f"(d[3]), "=f"(d[4]), "=f"(d[5]), "=f"(d[6]), "=f"(d[7]), "=f"(d[8]), "=f"(d[9]), "=f"(d[10]), "=f"(d[11])
    : "r"(a0), "r"(a1), "r"(a2), "r"(a3), "l"(db));
}
__device__ __forceinline__ void wgmma_rs24(float* d, uint32_t a0, uint32_t a1, uint32_t a2, uint32_t a3, uint64_t db) {
  asm volatile(
      "wgmma.mma_async.sync.aligned.m64n24k16.f32.bf16.bf16 {"
      "%0, %1, %2, %3, %4, %5, %6, %7, %8, %9, %10, %11"
      "}, {%12, %13, %14, %15}, %16, 1, 1, 1, 1;"
    : "+f"(d[0]), "+f"(d[1]), "+f"(d[2]), "+f"(d[3]), "+f"(d[4]), "+f"(d[5]), "+f"(d[6]), "+f"(d[7]), "+f"(d[8]), "+f"(d[9]), "+f"(d[10]), "+f"(d[11])
    : "r"(a0), "r"(a1), "r"(a2), "r"(a3), "l"(db));
}
__device__ __forceinline__ void wgmma_rs80_init(float* d, uint32_t a0, uint32_t a1, uint32_t a2, uint32_t a3, uint64_t db) {
  asm volatile(
      "wgmma.mma_async.sync.aligned.m64n80k16.f32.bf16.bf16 {"
      "%0, %1, %2, %3, %4, %5, %6, %7, %8, %9, %10, %11, %12, %13, %14, %15, %16, %17, %18, %19, %20, %21, %22, %23, %24, %25, %26, %27, %28, %29, %30, %31, "
      "%32, %33, %34, %35, %36, %37, %38, %39"
      "}, {%40, %41, %42, %43}, %44, 0, 1, 1, 1;"
    : "=f"(d[0]), "=f"(d[1]), "=f"(d[2]), "=f"(d[3]), "=f"(d[4]), "=f"(d[5]), "=f"(d[6]), "=f"(d[7]), "=f"(d[8]), "=f"(d[9]), "=f"(d[10]), "=f"(d[11]),
      "=f"(d[12]), "=f"(d[13]), "=f"(d[14]), "=f"(d[15]), "=f"(d[16]), "=f"(d[17]), "=f"(d[18]), "=f"(d[19]), "=f"(d[20]), "=f"(d[21]), "=f"(d[22]),
      "=f"(d[23]), "=f"(d[24]), "=f"(d[25]), "=f"(d[26]), "=f"(d[27]), "=f"(d[28]), "=f"(d[29]), "=f"(d[30]), "=f"(d[31]), "=f"(d[32]), "=f"(d[33]),
      "=f"(d[34]), "=f"(d[35]), "=f"(d[36]), "=f"(d[37]), "=f"(d[38]), "=f"(d[39])
    : "r"(a0), "r"(a1), "r"(a2), "r"(a3), "l"(db));
}
__device__ __forceinline__ void wgmma_rs80(float* d, uint32_t a0, uint32_t a1, uint32_t a2, uint32_t a3, uint64_t db) {
  asm volatile(
      "wgmma.mma_async.sync.aligned.m64n80k16.f32.bf16.bf16 {"
      "%0, %1, %2, %3, %4, %5, %6, %7, %8, %9, %10, %11, %12, %13, %14, %15, %16, %17, %18, %19, %20, %21, %22, %23, %24, %25, %26, %27, %28, %29, %30, %31, "
      "%32, %33, %34, %35, %36, %37, %38, %39"
      "}, {%40, %41, %42, %43}, %44, 1, 1, 1, 1;"
    : "+f"(d[0]), "+f"(d[1]), "+f"(d[2]), "+f"(d[3]), "+f"(d[4]), "+f"(d[5]), "+f"(d[6]), "+f"(d[7]), "+f"(d[8]), "+f"(d[9]), "+f"(d[10]), "+f"(d[11]),
      "+f"(d[12]), "+f"(d[13]), "+f"(d[14]), "+f"(d[15]), "+f"(d[16]), "+f"(d[17]), "+f"(d[18]), "+f"(d[19]), "+f"(d[20]), "+f"(d[21]), "+f"(d[22]),
      "+f"(d[23]), "+f"(d[24]), "+f"(d[25]), "+f"(d[26]), "+f"(d[27]), "+f"(d[28]), "+f"(d[29]), "+f"(d[30]), "+f"(d[31]), "+f"(d[32]), "+f"(d[33]),
      "+f"(d[34]), "+f"(d[35]), "+f"(d[36]), "+f"(d[37]), "+f"(d[38]), "+f"(d[39])
    : "r"(a0), "r"(a1), "r"(a2), "r"(a3), "l"(db));
}
__device__ __forceinline__ void wgmma_rs192_init(float* d, uint32_t a0, uint32_t a1, uint32_t a2, uint32_t a3, uint64_t db) {
  asm volatile(
      "wgmma.mma_async.sync.aligned.m64n192k16.f32.bf16.bf16 {"
      "%0, %1, %2, %3, %4, %5, %6, %7, %8, %9, %10, %11, %12, %13, %14, %15, %16, %17, %18, %19, %20, %21, %22, %23, %24, %25, %26, %27, %28, %29, %30, %31, "
      "%32, %33, %34, %35, %36, %37, %38, %39, %40, %41, %42, %43, %44, %45, %46, %47, %48, %49, %50, %51, %52, %53, %54, %55, %56, %57, %58, %59, %60, %61, "
      "%62, %63, %64, %65, %66, %67, %68, %69, %70, %71, %72, %73, %74, %75, %76, %77, %78, %79, %80, %81, %82, %83, %84, %85, %86, %87, %88, %89, %90, %91, "
      "%92, %93, %94, %95"
      "}, {%96, %97, %98, %99}, %100, 0, 1, 1, 1;"
    : "=f"(d[0]), "=f"(d[1]), "=f"(d[2]), "=f"(d[3]), "=f"(d[4]), "=f"(d[5]), "=f"(d[6]), "=f"(d[7]), "=f"(d[8]), "=f"(d[9]), "=f"(d[10]), "=f"(d[11]),
      "=f"(d[12]), "=f"(d[13]), "=f"(d[14]), "=f"(d[15]), "=f"(d[16]), "=f"(d[17]), "=f"(d[18]), "=f"(d[19]), "=f"(d[20]), "=f"(d[21]), "=f"(d[22]),
      "=f"(d[23]), "=f"(d[24]), "=f"(d[25]), "=f"(d[26]), "=f"(d[27]), "=f"(d[28]), "=f"(d[29]), "=f"(d[30]), "=f"(d[31]), "=f"(d[32]), "=f"(d[33]),
      "=f"(d[34]), "=f"(d[35]), "=f"(d[36]), "=f"(d[37]), "=f"(d[38]), "=f"(d[39]), "=f"(d[40]), "=f"(d[41]), "=f"(d[42]), "=f"(d[43]), "=f"(d[44]),
      "=f"(d[45]), "=f"(d[46]), "=f"(d[47]), "=f"(d[48]), "=f"(d[49]), "=f"(d[50]), "=f"(d[51]), "=f"(d[52]), "=f"(d[53]), "=f"(d[54]), "=f"(d[55]),
      "=f"(d[56]), "=f"(d[57]), "=f"(d[58]), "=f"(d[59]), "=f"(d[60]), "=f"(d[61]), "=f"(d[62]), "=f"(d[63]), "=f"(d[64]), "=f"(d[65]), "=f"(d[66]),
      "=f"(d[67]), "=f"(d[68]), "=f"(d[69]), "=f"(d[70]), "=f"(d[71]), "=f"(d[72]), "=f"(d[73]), "=f"(d[74]), "=f"(d[75]), "=f"(d[76]), "=f"(d[77]),
      "=f"(d[78]), "=f"(d[79]), "=f"(d[80]), "=f"(d[81]), "=f"(d[82]), "=f"(d[83]), "=f"(d[84]), "=f"(d[85]), "=f"(d[86]), "=f"(d[87]), "=f"(d[88]),
      "=f"(d[89]), "=f"(d[90]), "=f"(d[91]), "=f"(d[92]), "=f"(d[93]), "=f"(d[94]), "=f"(d[95])
    : "r"(a0), "r"(a1), "r"(a2), "r"(a3), "l"(db));
}
__device__ __forceinline__ void wgmma_rs192(float* d, uint32_t a0, uint32_t a1, uint32_t a2, uint32_t a3, uint64_t db) {
  asm volatile(
      "wgmma.mma_async.sync.aligned.m64n192k16.f32.bf16.bf16 {"
      "%0, %1, %2, %3, %4, %5, %6, %7, %8, %9, %10, %11, %12, %13, %14, %15, %16, %17, %18, %19, %20, %21, %22, %23, %24, %25, %26, %27, %28, %29, %30, %31, "
      "%32, %33, %34, %35, %36, %37, %38, %39, %40, %41, %42, %43, %44, %45, %46, %47, %48, %49, %50, %51, %52, %53, %54, %55, %56, %57, %58, %59, %60, %61, "
      "%62, %63, %64, %65, %66, %67, %68, %69, %70, %71, %72, %73, %74, %75, %76, %77, %78, %79, %80, %81, %82, %83, %84, %85, %86, %87, %88, %89, %90, %91, "
      "%92, %93, %94, %95"
      "}, {%96, %97, %98, %99}, %100, 1, 1, 1, 1;"
    : "+f"(d[0]), "+f"(d[1]), "+f"(d[2]), "+f"(d[3]), "+f"(d[4]), "+f"(d[5]), "+f"(d[6]), "+f"(d[7]), "+f"(d[8]), "+f"(d[9]), "+f"(d[10]), "+f"(d[11]),
      "+f"(d[12]), "+f"(d[13]), "+f"(d[14]), "+f"(d[15]), "+f"(d[16]), "+f"(d[17]), "+f"(d[18]), "+f"(d[19]), "+f"(d[20]), "+f"(d[21]), "+f"(d[22]),
      "+f"(d[23]), "+f"(d[24]), "+f"(d[25]), "+f"(d[26]), "+f"(d[27]), "+f"(d[28]), "+f"(d[29]), "+f"(d[30]), "+f"(d[31]), "+f"(d[32]), "+f"(d[33]),
      "+f"(d[34]), "+f"(d[35]), "+f"(d[36]), "+f"(d[37]), "+f"(d[38]), "+f"(d[39]), "+f"(d[40]), "+f"(d[41]), "+f"(d[42]), "+f"(d[43]), "+f"(d[44]),
      "+f"(d[45]), "+f"(d[46]), "+f"(d[47]), "+f"(d[48]), "+f"(d[49]), "+f"(d[50]), "+f"(d[51]), "+f"(d[52]), "+f"(d[53]), "+f"(d[54]), "+f"(d[55]),
      "+f"(d[56]), "+f"(d[57]), "+f"(d[58]), "+f"(d[59]), "+f"(d[60]), "+f"(d[61]), "+f"(d[62]), "+f"(d[63]), "+f"(d[64]), "+f"(d[65]), "+f"(d[66]),
      "+f"(d[67]), "+f"(d[68]), "+f"(d[69]), "+f"(d[70]), "+f"(d[71]), "+f"(d[72]), "+f"(d[73]), "+f"(d[74]), "+f"(d[75]), "+f"(d[76]), "+f"(d[77]),
      "+f"(d[78]), "+f"(d[79]), "+f"(d[80]), "+f"(d[81]), "+f"(d[82]), "+f"(d[83]), "+f"(d[84]), "+f"(d[85]), "+f"(d[86]), "+f"(d[87]), "+f"(d[88]),
      "+f"(d[89]), "+f"(d[90]), "+f"(d[91]), "+f"(d[92]), "+f"(d[93]), "+f"(d[94]), "+f"(d[95])
    : "r"(a0), "r"(a1), "r"(a2), "r"(a3), "l"(db));
}
__device__ __forceinline__ void wgmma_rs48_init(float* d, uint32_t a0, uint32_t a1, uint32_t a2, uint32_t a3, uint64_t db) {
  asm volatile(
      "wgmma.mma_async.sync.aligned.m64n48k16.f32.bf16.bf16 {"
      "%0, %1, %2, %3, %4, %5, %6, %7, %8, %9, %10, %11, %12, %13, %14, %15, %16, %17, %18, %19, %20, %21, %22, %23"
      "}, {%24, %25, %26, %27}, %28, 0, 1, 1, 1;"
    : "=f"(d[0]), "=f"(d[1]), "=f"(d[2]), "=f"(d[3]), "=f"(d[4]), "=f"(d[5]), "=f"(d[6]), "=f"(d[7]), "=f"(d[8]), "=f"(d[9]), "=f"(d[10]), "=f"(d[11]),
      "=f"(d[12]), "=f"(d[13]), "=f"(d[14]), "=f"(d[15]), "=f"(d[16]), "=f"(d[17]), "=f"(d[18]), "=f"(d[19]), "=f"(d[20]), "=f"(d[21]), "=f"(d[22]),
      "=f"(d[23])
    : "r"(a0), "r"(a1), "r"(a2), "r"(a3), "l"(db));
}
__device__ __forceinline__ void wgmma_rs48(float* d, uint32_t a0, uint32_t a1, uint32_t a2, uint32_t a3, uint64_t db) {
  asm volatile(
      "wgmma.mma_async.sync.aligned.m64n48k16.f32.bf16.bf16 {"
      "%0, %1, %2, %3, %4, %5, %6, %7, %8, %9, %10, %11, %12, %13, %14, %15, %16, %17, %18, %19, %20, %21, %22, %23"
      "}, {%24, %25, %26, %27}, %28, 1, 1, 1, 1;"
    : "+f"(d[0]), "+f"(d[1]), "+f"(d[2]), "+f"(d[3]), "+f"(d[4]), "+f"(d[5]), "+f"(d[6]), "+f"(d[7]), "+f"(d[8]), "+f"(d[9]), "+f"(d[10]), "+f"(d[11]),
      "+f"(d[12]), "+f"(d[13]), "+f"(d[14]), "+f"(d[15]), "+f"(d[16]), "+f"(d[17]), "+f"(d[18]), "+f"(d[19]), "+f"(d[20]), "+f"(d[21]), "+f"(d[22]),
      "+f"(d[23])
    : "r"(a0), "r"(a1), "r"(a2), "r"(a3), "l"(db));
}

__device__ __forceinline__ uint32_t s2u(const void* p) { return (uint32_t)__cvta_generic_to_shared(p); }
__device__ __forceinline__ void mbar_init(uint32_t b, int c) { asm volatile("mbarrier.init.shared::cta.b64 [%0], %1;" :: "r"(b), "r"(c)); }
__device__ __forceinline__ void mbar_expect(uint32_t b, int bytes) { asm volatile("mbarrier.arrive.expect_tx.shared::cta.b64 _, [%0], %1;" :: "r"(b), "r"(bytes) : "memory"); }
__device__ __forceinline__ void mbar_arrive(uint32_t b) { asm volatile("mbarrier.arrive.shared::cta.b64 _, [%0];" :: "r"(b) : "memory"); }
__device__ __forceinline__ void mbar_arrive_n(uint32_t b, int n) { asm volatile("mbarrier.arrive.shared::cta.b64 _, [%0], %1;" :: "r"(b), "r"(n) : "memory"); }
__device__ __forceinline__ void mbar_arrive_cl(uint32_t b) { asm volatile("mbarrier.arrive.shared::cluster.b64 _, [%0];" :: "r"(b) : "memory"); }
__device__ __forceinline__ void mbar_wait(uint32_t b, int ph) {
  asm volatile("{\n.reg .pred p;\nW: mbarrier.try_wait.parity.shared::cta.b64 p, [%0], %1;\n@!p bra W;\n}" :: "r"(b), "r"(ph) : "memory");
}
__device__ __forceinline__ uint32_t mapa(uint32_t a, uint32_t cta) { uint32_t r; asm("mapa.shared::cluster.u32 %0, %1, %2;" : "=r"(r) : "r"(a), "r"(cta)); return r; }
__device__ __forceinline__ void tma2d(uint32_t dst, const CUtensorMap* m, int c0, int c1, uint32_t bar) {
  asm volatile("cp.async.bulk.tensor.2d.shared::cluster.global.mbarrier::complete_tx::bytes [%0], [%1, {%3, %4}], [%2];"
               :: "r"(dst), "l"(m), "r"(bar), "r"(c0), "r"(c1) : "memory");
}
__device__ __forceinline__ void tma3d(uint32_t dst, const CUtensorMap* m, int c0, int c1, int c2, uint32_t bar) {
  asm volatile("cp.async.bulk.tensor.3d.shared::cluster.global.mbarrier::complete_tx::bytes [%0], [%1, {%3, %4, %5}], [%2];"
               :: "r"(dst), "l"(m), "r"(bar), "r"(c0), "r"(c1), "r"(c2) : "memory");
}
__device__ __forceinline__ void bulk_mc(uint32_t dst, const void* src, int bytes, uint32_t bar) {
  asm volatile("cp.async.bulk.shared::cluster.global.mbarrier::complete_tx::bytes.multicast::cluster [%0], [%1], %2, [%3], %4;"
               :: "r"(dst), "l"(src), "r"(bytes), "r"(bar), "h"((uint16_t)3) : "memory");
}
__device__ __forceinline__ void tma3d_mc(uint32_t dst, const CUtensorMap* m, int c0, int c1, int c2, uint32_t bar) {
  asm volatile("cp.async.bulk.tensor.3d.shared::cluster.global.mbarrier::complete_tx::bytes.multicast::cluster [%0], [%1, {%3, %4, %5}], [%2], %6;"
               :: "r"(dst), "l"(m), "r"(bar), "r"(c0), "r"(c1), "r"(c2), "h"((uint16_t)3) : "memory");
}
__device__ __forceinline__ void bulk_ld(uint32_t dst, const void* src, int bytes, uint32_t bar) {
  asm volatile("cp.async.bulk.shared::cluster.global.mbarrier::complete_tx::bytes [%0], [%1], %2, [%3];" :: "r"(dst), "l"(src), "r"(bytes), "r"(bar) : "memory");
}
__device__ __forceinline__ void bulk_st(void* dst, uint32_t src, int bytes) {
  asm volatile("cp.async.bulk.global.shared::cta.bulk_group [%0], [%1], %2;" :: "l"(dst), "r"(src), "r"(bytes) : "memory");
}
__device__ __forceinline__ void tma2d_st(const CUtensorMap* m, int c0, int c1, uint32_t src) {
  asm volatile("cp.async.bulk.tensor.2d.global.shared::cta.bulk_group [%0, {%2, %3}], [%1];" :: "l"(m), "r"(src), "r"(c0), "r"(c1) : "memory");
}
__device__ __forceinline__ void bulk_wait_read() { asm volatile("cp.async.bulk.commit_group;\ncp.async.bulk.wait_group.read 0;" ::: "memory"); }
__device__ __forceinline__ void bulk_wait() { asm volatile("cp.async.bulk.commit_group;\ncp.async.bulk.wait_group 0;" ::: "memory"); }
__device__ __forceinline__ void l2_prefetch(const void* p, int bytes) { asm volatile("cp.async.bulk.prefetch.L2.global [%0], %1;" :: "l"(p), "r"(bytes) : "memory"); }
__device__ __forceinline__ void fence_async_smem() { asm volatile("fence.proxy.async.shared::cta;" ::: "memory"); }
__device__ __forceinline__ void fence_gpu() { asm volatile("fence.release.gpu;" ::: "memory"); }
__device__ __forceinline__ void flag_add(unsigned* p, unsigned n = 1) { asm volatile("red.relaxed.gpu.global.add.u32 [%0], %1;" :: "l"(p), "r"(n) : "memory"); }
__device__ __forceinline__ void flag_set(unsigned* p) { fence_gpu(); flag_add(p); }
__device__ __forceinline__ unsigned ld_flag(const unsigned* p) { unsigned v; asm volatile("ld.relaxed.gpu.global.u32 %0, [%1];" : "=r"(v) : "l"(p) : "memory"); return v; }
__device__ __forceinline__ void flag_wait(const unsigned* p, unsigned target) {
#pragma unroll 1
  for (int n = 0; !__all_sync(~0u, (int)(ld_flag(p) - target) >= 0); n++) if (n > (1 << 22)) __trap();
  asm volatile("fence.acquire.gpu;\nfence.proxy.async.global;" ::: "memory");
}
__device__ constexpr uint32_t dlo(uint32_t off, uint32_t lbo) { return (off >> 4) | ((lbo >> 4) << 16); }
__device__ constexpr uint32_t dhi(uint32_t sbo, uint32_t sw) { return (sbo >> 4) | (sw << 30); }
__device__ __forceinline__ uint64_t desc(uint32_t lo, uint32_t hi) { return (uint64_t)lo | ((uint64_t)hi << 32); }
__device__ __forceinline__ void wg_fence() { asm volatile("wgmma.fence.sync.aligned;" ::: "memory"); }
__device__ __forceinline__ void wg_commit() { asm volatile("wgmma.commit_group.sync.aligned;" ::: "memory"); }
template <int N> __device__ __forceinline__ void wg_wait() { asm volatile("wgmma.wait_group.sync.aligned %0;" :: "n"(N) : "memory"); }
template <int N> __device__ __forceinline__ void zero(float (&d)[N]) {
#pragma unroll
  for (int k = 0; k < N; k++) d[k] = 0.f;
}
template <int N> __device__ __forceinline__ void pin(float (&d)[N]) {
#pragma unroll
  for (int k = 0; k < N; k++) asm volatile("" : "+f"(d[k]) :: "memory");
}
__device__ __forceinline__ uint32_t pack(float lo, float hi) { uint32_t r; asm("cvt.rn.bf16x2.f32 %0, %1, %2;" : "=r"(r) : "f"(hi), "f"(lo)); return r; }
__device__ __forceinline__ float blo(uint32_t w) { return __uint_as_float(w << 16); }
__device__ __forceinline__ float bhi(uint32_t w) { return __uint_as_float(w & 0xffff0000u); }
__device__ __forceinline__ void sts32(uint32_t a, uint32_t v) { asm volatile("st.shared.b32 [%0], %1;" :: "r"(a), "r"(v) : "memory"); }
__device__ __forceinline__ void stg32(void* p, uint32_t v) { asm volatile("st.global.b32 [%0], %1;" :: "l"(p), "r"(v) : "memory"); }
__device__ __forceinline__ uint4 lds128(uint32_t a) { uint4 v; asm volatile("ld.shared.v4.b32 {%0,%1,%2,%3}, [%4];" : "=r"(v.x), "=r"(v.y), "=r"(v.z), "=r"(v.w) : "r"(a)); return v; }
__device__ __forceinline__ float2 lds64f(uint32_t a) { float2 v; asm volatile("ld.shared.v2.f32 {%0,%1}, [%2];" : "=f"(v.x), "=f"(v.y) : "r"(a)); return v; }
__device__ __forceinline__ float4 lds128f(uint32_t a) { float4 v; asm volatile("ld.shared.v4.f32 {%0,%1,%2,%3}, [%4];" : "=f"(v.x), "=f"(v.y), "=f"(v.z), "=f"(v.w) : "r"(a)); return v; }
__device__ __forceinline__ uint32_t lds32(uint32_t a) { uint32_t v; asm volatile("ld.shared.b32 %0, [%1];" : "=r"(v) : "r"(a)); return v; }
__device__ __forceinline__ uint4 ldg_cg128(const void* p) { uint4 v; asm volatile("ld.global.cg.v4.b32 {%0,%1,%2,%3}, [%4];" : "=r"(v.x), "=r"(v.y), "=r"(v.z), "=r"(v.w) : "l"(p)); return v; }
__device__ __forceinline__ float ex2(float x) { float y; asm("ex2.approx.ftz.f32 %0, %1;" : "=f"(y) : "f"(x)); return y; }
__device__ __forceinline__ float tanh_(float x) { float y; asm("tanh.approx.f32 %0, %1;" : "=f"(y) : "f"(x)); return y; }
__device__ __forceinline__ bool elect() { uint32_t p; asm volatile("{\n.reg .pred q;\nelect.sync _|q, 0xffffffff;\nselp.u32 %0, 1, 0, q;\n}" : "=r"(p)); return p; }
__device__ __forceinline__ void prefetch_map(const CUtensorMap* m) { asm volatile("prefetch.tensormap [%0];" :: "l"(m) : "memory"); }
__device__ __forceinline__ void cluster_arrive() { asm volatile("barrier.cluster.arrive.relaxed.aligned;" ::: "memory"); }
__device__ __forceinline__ void cluster_wait() { asm volatile("barrier.cluster.wait.aligned;" ::: "memory"); }

template <int N> struct Ring {
  int s, ph;
  __device__ __forceinline__ void adv() { if (++s == N) { s = 0; ph ^= 1; } }
};

__device__ __forceinline__ int kv_unit(int p) { return 4 - 4 * p; }
__device__ __forceinline__ int korder(int b, int j) { return b == 0 ? j : b - (b <= j); }
__device__ __forceinline__ int hslice(int j) { return 27 * j + (j & 1); }
constexpr int HE = 7;
__device__ __forceinline__ int hlate(int j) { return 8 * HE + (27 - 2 * HE) * (j >> 1) + (14 - HE) * (j & 1); }
__device__ __forceinline__ int hother(int p, int j) { p += p >= HE * j ? HE : 0; return p + (p >= hlate(j) ? 14 - HE - (j & 1) : 0); }
__device__ __forceinline__ unsigned epoch(uint32_t sb) { unsigned e; mbar_wait(sb + B_EP, 0); asm volatile("ld.shared.u32 %0, [%1];" : "=r"(e) : "r"(sb + SM_EPOCH)); return e; }

__device__ __forceinline__ void producer_w(const Maps& m, uint32_t sb, int rank, int i, int j) {
  Ring<NU> r{0, 1};
  const uint32_t full = sb + B_WFULL, empty = sb + B_WEMPTY;
  const unsigned char* img = g_img + j * IMG_BYTES;
#pragma unroll 1
  for (int k = 0; k < 20; k++) {
    int row = 32 * k + 16 * rank + 40 * (i & ~1);
    if (row >= D_) row -= D_;
    mbar_wait(empty + 8 * r.s, r.ph);
    if (elect()) {
      mbar_expect(full + 8 * r.s, UNIT);
      tma3d_mc(sb + r.s * UNIT + rank * 6144, &m.q64, 80 * j, row, 0, full + 8 * r.s);
      tma3d_mc(sb + r.s * UNIT + 12288 + rank * 1536, &m.q16, 80 * j + 64, row, 0, full + 8 * r.s);
    }
    r.adv();
  }
#pragma unroll 1
  for (int l = 0;; l++) {
#pragma unroll 1
    for (int k = 0; k < 8; k++) {
      mbar_wait(empty + 8 * r.s, r.ph);
      if (elect()) {
        if (k & 2) mbar_arrive(full + 8 * r.s); else mbar_expect(full + 8 * r.s, 20480);
        if (k == 3) mbar_arrive_n(sb + B_KVFREE, 2);
        if (k == 7) mbar_arrive(sb + B_KVFREE + 8);
      }
      r.adv();
    }
#pragma unroll 1
    for (int k = 0; k < 8; k++) {
      mbar_wait(empty + 8 * r.s, r.ph);
      if (elect()) {
        mbar_expect(full + 8 * r.s, 12800);
        const int row = 160 * (k & 3) + 40 * (k >> 2) + 80 * rank;
#pragma unroll
        for (int g = 0; g < 5; g++) tma3d_mc(sb + r.s * UNIT + rank * 6400 + g * 1280, &m.wo, 0, row + 8 * g, 5 * j, full + 8 * r.s);
      }
      r.adv();
    }
    if (l == 0) flag_wait(g_flags + FL_CS + 8 + j, epoch(sb) * 16);
#pragma unroll 1
    for (int g2 = 0; g2 < 2; g2++) {
      if (g2) {
        const unsigned char* s = img + IMG_2;
#pragma unroll 1
        for (int k = 0; k < 24; k++) {
          mbar_wait(empty + 8 * r.s, r.ph);
          if (elect()) {
            const int bytes = k == 2 ? 10240 : k < 22 ? 12800 : 0;
            mbar_expect(full + 8 * r.s, bytes);
            if (!bytes) mbar_arrive_n(empty + 8 * r.s, 16);
            else if ((k & 1) == rank) bulk_mc(sb + r.s * UNIT, s, bytes, full + 8 * r.s);
          }
          s += k == 2 ? 10240 : 12800;
          r.adv();
        }
        if (l == NPH / 2 - 1) return;
      }
      const int blob = g2 ? 7680 : 7168, a = g2 ? 6144 : 7168;
      const unsigned char* base = img + (g2 ? IMG_Q : IMG_1);
#pragma unroll 1
      for (int k = 0; k < 20; k++) {
        const int s = 2 * k + rank, b = (s * 52) >> 8, st = s + 5 * (korder(b, j) - b);
        mbar_wait(empty + 8 * r.s, r.ph);
        if (elect()) {
          mbar_expect(full + 8 * r.s, 2 * blob);
          bulk_mc(sb + r.s * UNIT + rank * a, base + st * blob, a, full + 8 * r.s);
          if (g2) bulk_mc(sb + r.s * UNIT + 12288 + rank * 1536, base + st * blob + 6144, 1536, full + 8 * r.s);
        }
        r.adv();
      }
    }
  }
}

__device__ __forceinline__ void ln_scale(bool MLP, float s, float q, float& rs, float& nm) {
  const float mean = s * (1.f / D_), var = fmaxf(fmaf(-mean, mean, q * (1.f / D_)), 0.f);
  rs = rsqrtf(var + 1e-5f);
  if (MLP) rs *= 0.5f * rsqrtf(var * rs * rs + 1e-5f);
  nm = -mean * rs;
}

__device__ __forceinline__ void producer_a(const Maps& m, const Params& P, uint32_t sb, int i, int j, int wg, int lane) {
  const int hb = 2 * i + wg;
  const uint32_t aslot = sb + SM_A + wg * NA * ASLOT, afull = sb + B_AFULL + wg * NA * 8, aempty = sb + B_AEMPTY + wg * NA * 8;
  const uint32_t staged = sb + B_STAGED + wg * 32;
  unsigned* fl = g_flags + hb * 64;
  Ring<NA> r{0, 1};
  Ring<4> st{0, 0};
  if (elect()) { mbar_expect(afull, 10240); tma2d(aslot, &m.xr, 80 * j, 64 * hb, afull); }
  r.adv();
#pragma unroll 1
  for (int b = 0; b < 8; b++) {
    mbar_wait(aempty + 8 * r.s, r.ph);
    if (elect()) {
      mbar_expect(afull + 8 * r.s, 10240);
      const int c0 = 80 * ((b + (i >> 1)) & 7);
      tma2d(aslot + r.s * ASLOT, &m.x0, c0, 64 * hb, afull + 8 * r.s); tma2d(aslot + r.s * ASLOT + 8192, &m.x16, c0 + 64, 64 * hb, afull + 8 * r.s);
    }
    r.adv();
    if (b == 3) cluster_wait();
  }
  const unsigned ep = epoch(sb);
  auto row_factors = [&](int ph) {
#pragma unroll 1
    for (int k = 0; k < 2; k++) {
      const float2* src = g_st + ((ph * 32 + hb) * 64 + 32 * k + lane) * 8;
      uint4 v[4];
#pragma unroll
      for (int e = 0; e < 4; e++) v[e] = ldg_cg128(src + 2 * e);
      float s = 0.f, q = 0.f;
#pragma unroll
      for (int e = 0; e < 4; e++) { s += __uint_as_float(v[e].x) + __uint_as_float(v[e].z); q += __uint_as_float(v[e].y) + __uint_as_float(v[e].w); }
      ln_scale(ph & 1, s, q, s, q);
      asm volatile("st.shared.v2.f32 [%0], {%1, %2};" :: "r"(sb + SM_LN + (wg * 64 + 32 * k + lane) * 8), "f"(s), "f"(q) : "memory");
    }
    __syncwarp();
    if (elect()) mbar_arrive_n(sb + B_ST + 8 * wg, 4);
  };
#pragma unroll 1
  for (int sg = 0; sg < 7 * (NPH / 2); sg++) {
    const int l = sg >= 7, s = sg - 7 * l;
    if (s == 0 || s == 4) {
      if (l == 0) {
        const int m = s >> 2, n4 = m ? 28 : 30, c4 = wg * n4 + min(lane, n4 - 1);
        mbar_wait(sb + B_CSQ + 8 * m, 0);
        float4 a = make_float4(0.f, 0.f, 0.f, 0.f);
        const float* src = g_cs + (m * 128 + j) * 240 + 4 * c4;
#pragma unroll 1
        for (int k = 0; k < 4; k++, src += 4 * 8 * 240) {
          uint4 v[4];
#pragma unroll
          for (int e = 0; e < 4; e++) v[e] = ldg_cg128(src + e * 8 * 240);
#pragma unroll
          for (int e = 0; e < 4; e++) { a.x += __uint_as_float(v[e].x); a.y += __uint_as_float(v[e].y); a.z += __uint_as_float(v[e].z); a.w += __uint_as_float(v[e].w); }
        }
        const uint32_t sp = 4 << m, d = sb + (m ? SM_CB1 : SM_CSQ) + 4 * sp * c4;
        sts32(d, __float_as_uint(a.x)); sts32(d + sp, __float_as_uint(a.y)); sts32(d + 2 * sp, __float_as_uint(a.z)); sts32(d + 3 * sp, __float_as_uint(a.w));
      }
      row_factors(2 * l + (s >> 2));
    }
    unsigned* rf = s == 0 ? g_flags + (2 * i + 2) * 64 + FL_KV + l * 16 + j * 2
                          : fl + (s < 3 ? FL_O + l * 2 + s - 1 : s == 3 ? FL_X + 2 * l : s < 6 ? FL_H + l * 2 + s - 4 : FL_X + 1);
    const unsigned* wf = s ? rf : rf - 128 + wg;
    const unsigned target = ep * (s ? 8 : 2 * min(i, 2));
    const int sx = r.s;
#pragma unroll 1
    for (int k = sg == 0 ? 3 : 0; k > 0; k--) {
      mbar_wait(aempty + 8 * r.s, r.ph);
      if (elect()) mbar_arrive(afull + 8 * r.s);
      r.adv();
    }
    if (sg == 0) if (elect()) mbar_arrive(sb + B_PREP);
    if (s == 3 || s == 6) {
      mbar_wait(aempty + 8 * r.s, r.ph);
      if (elect()) {
        mbar_expect(afull + 8 * r.s, 10240);
        if (sg == 3) tma2d(aslot + r.s * ASLOT, &m.xr, 80 * j, 64 * hb, afull + 8 * r.s);
        else bulk_ld(aslot + r.s * ASLOT, g_act + ((s == 3 ? G_X2 : G_X1) + (hb * 80 + 10 * j) * 1024), 10240, afull + 8 * r.s);
      }
      r.adv();
    }
    if (s != 5) {
      mbar_wait(staged + 8 * st.s, st.ph); st.adv();
      if (sg == 7 * (NPH / 2) - 1) {
        if (elect()) { tma2d_st(&m.out, 80 * j, 64 * hb, aslot + sx * ASLOT); bulk_wait_read(); }
        break;
      }
      if (elect()) { flag_set(rf); if (s == 0) flag_add(rf + 128); }
    }
    if (s == 0 && wg) if (elect()) mbar_arrive(sb + B_GO);
    const bool hid = s == 4 || s == 5;
    const unsigned char* base = g_act + (s == 0 ? G_KV + ((l * 8 + j) * 2 + wg) * 327680 + (i - 2) * 2048
                                                : (s < 3 ? G_O + 5120 * (s - 1) : hid ? G_H : s == 3 ? G_X1 : G_X2) + hb * (hid ? 216 * 1024 : 80 * 1024));
    const int n = s < 3 ? 4 : s == 4 ? 7 * HE / 5 : s == 5 ? 19 : 7;
    int k = s == 5 ? 7 * HE / 5 : 0, o0 = 0, o1 = 0, first = 0, bytes = 0;
    auto claim = [&]() {
      o0 = s < 3 ? k * 20480 : korder(k + 1, j) * 10240; first = 5120; o1 = o0 + (s < 3 ? 10240 : 5120); bytes = 10240;
      if (hid) {
        const int p0 = hother(5 * k, j), p4 = hother(5 * k + 4, j), gap = p4 - p0 - 4;
        o0 = p0 * 2048;
        if (gap) first = ((p0 < HE * j ? HE * j : hlate(j)) - p0) * 2048;
        o1 = o0 + first + gap * 2048;
        if (p4 == 108) bytes = 8192;
      }
      mbar_wait(aempty + 8 * r.s, r.ph);
      if (elect()) mbar_expect(afull + 8 * r.s, bytes);
    };
    auto issue = [&]() {
      if (elect()) {
        bulk_ld(aslot + r.s * ASLOT, base + o0, first, afull + 8 * r.s);
        bulk_ld(aslot + r.s * ASLOT + first, base + o1, bytes - first, afull + 8 * r.s);
      }
      r.adv();
    };
    if (s == 0) mbar_wait(sb + B_KVFREE + 8 * wg, l); else claim();
    if (s == 5) { mbar_wait(sb + B_HL, l); asm volatile("fence.proxy.async.global;" ::: "memory"); }
    else flag_wait(wf, target);
    if (s) {
      issue();
#pragma unroll 1
      for (k++; k < n; k++) { claim(); issue(); }
    }
    if (s == 0) {
      if (elect()) {
        const uint32_t d = sb + kv_unit(wg) * UNIT, f = sb + B_WFULL + 8 * kv_unit(wg);
        const unsigned char* junk = (const unsigned char*)P.wqkv;
        if (i == 1) {
#pragma unroll 1
          for (int gg = 0; gg < 10; gg++) {
            const uint32_t fb = f + (gg >= 5 ? 8 : 0);
            bulk_ld(d + gg * 6144, junk, 2048, fb); bulk_ld(d + gg * 6144 + 2048, base + gg * 32768 + 2048, 2048, fb);
          }
        } else {
          const unsigned char* bb = i ? base : junk;
#pragma unroll 1
          for (int gg = 0; gg < 5; gg++) bulk_ld(d + gg * 6144, bb + gg * 32768, 4096, f);
#pragma unroll 1
          for (int gg = 5; gg < 10; gg++) bulk_ld(d + gg * 6144, bb + gg * 32768, 4096, f + 8);
        }
      }
      if (wg == 0) if (elect()) mbar_arrive(sb + B_GO);
    }
  }
}

__device__ __forceinline__ void misc_warp(const Maps& mp, const Params& P, uint32_t sb, int i, int j, int lane) {
  unsigned ep = 0;
  if (elect()) {
    ep = (atomicAdd(&g_ticket, 1) >> 7) + 1;
    asm volatile("st.shared.u32 [%0], %1;" :: "r"(sb + SM_EPOCH), "r"(ep) : "memory");
    mbar_arrive(sb + B_EP);
  }
  __syncwarp();
  cluster_wait();
  ep = epoch(sb);
  const int c1 = 8 * hslice(j);
  const int n1 = 3 - (i & 1), s1 = (5 * i + 1) >> 1, sq = (5 * i) >> 1, n2 = min(7, 109 - 7 * i);
  const uint32_t f = sb + B_PLD;
  unsigned char* img = g_img + j * IMG_BYTES;
  auto slot = [&](int k) { return sb + SM_A + ((k & 1) * NA + (4 + (k >> 1)) % NA) * ASLOT; };
  auto w2pos = [&](int k) { return k < 6 ? slot(k) + 7680 : slot(5); };
#pragma unroll 1
  for (int step = 0; step < NPH + 2; step++) {
    if (step == 0 || step == 2) {
      const int m = step >> 1;
      if (m == 0) {
        mbar_wait(sb + B_CSP, 0);
      } else {
        mbar_wait(sb + B_PREP, 0);
        if (elect()) {
          mbar_expect(f, n1 * 7168 + (5 - n1) * 7680 + n2 * 2560);
#pragma unroll 1
          for (int k = 0; k < 7; k++) {
            if (k < n1) tma3d(slot(k), &mp.w1i, 0, 16 * (s1 + k), c1 >> 4, f);
            else if (k < 5) { tma3d(slot(k), &mp.q64, 80 * j, 16 * (sq + k - n1), 0, f); tma3d(slot(k) + 6144, &mp.q16, 80 * j + 64, 16 * (sq + k - n1), 0, f); }
            if (k < n2) {
              const int s = 7 * i + k, t = hother(s - 14, j), tl = t - 8 * HE, u = tl / (27 - 2 * HE), v = tl - (27 - 2 * HE) * u, od = v >= 14 - HE;
              const int row = s < 14 ? c1 + 16 * s : tl < 0 ? 8 * hslice(t / HE) + 16 * (t % HE) : 8 * hslice(2 * u + od) + 16 * (HE + v - (14 - HE) * od);
              tma3d(w2pos(k), &mp.w2i, 0, row, 5 * j, f);
            }
          }
        }
        {
          uint4 b1 = {}, b2 = {};
          if (c1 + 8 * lane < F_ && lane < 28) b1 = ldg_cg128(P.b1 + c1 + 8 * lane);
          if (lane < 10) b2 = ldg_cg128(P.b2 + 80 * j + 8 * lane);
          const uint32_t u[4] = {b1.x, b1.y, b1.z, b1.w}, v[4] = {b2.x, b2.y, b2.z, b2.w};
      #pragma unroll
          for (int e = 0; e < 4; e++) {
            if (lane < 28) { sts32(sb + SM_CB1 + 64 * lane + 16 * e + 4, __float_as_uint(0.5f * blo(u[e]))); sts32(sb + SM_CB1 + 64 * lane + 16 * e + 12, __float_as_uint(0.5f * bhi(u[e]))); }
            if (lane < 20) { sts32(sb + SM_B2 + 32 * lane + 8 * e, v[e] << 16); sts32(sb + SM_B2 + 32 * lane + 8 * e + 4, v[e] & 0xffff0000u); }
          }
        }
        mbar_wait(f, 0);
        if (elect()) {
#pragma unroll 1
          for (int k = 0; k < 7; k++) {
            if (k < n1) bulk_st(img + IMG_1 + (s1 + k) * 7168, slot(k), 7168);
            else if (k < 5) bulk_st(img + IMG_Q + (sq + k - n1) * 7680, slot(k), 7680);
            if (k < n2) bulk_st(img + IMG_2 + (7 * i + k) * 2560, w2pos(k), 2560);
          }
        }
        float a[8] = {0, 0, 0, 0, 0, 0, 0, 0};
        const int grp = min(lane, 27);
#pragma unroll 1
        for (int k = 0; k < 4 * n1; k++) {
          const uint32_t p = slot(k >> 2) + (grp >> 1) * 512 + (k & 3) * 128 + (((grp ^ k) & 1) << 4);
          uint4 v[4];
#pragma unroll
          for (int e = 0; e < 4; e++) v[e] = lds128(p + 32 * e);
#pragma unroll
          for (int e = 0; e < 4; e++) {
            a[0] += blo(v[e].x); a[1] += bhi(v[e].x); a[2] += blo(v[e].y); a[3] += bhi(v[e].y);
            a[4] += blo(v[e].z); a[5] += bhi(v[e].z); a[6] += blo(v[e].w); a[7] += bhi(v[e].w);
          }
        }
        if (lane < 28) {
          float* dst = g_cs + (128 + i * 8 + j) * 240 + 8 * grp;
          *(float4*)dst = make_float4(a[0], a[1], a[2], a[3]); *(float4*)(dst + 4) = make_float4(a[4], a[5], a[6], a[7]);
        }
        __syncwarp();
        if (elect()) {
          bulk_wait_read();
#pragma unroll 1
          for (int k = 0; k < 6; k++) mbar_arrive_n(sb + B_AEMPTY + 8 * ((k & 1) * NA + (4 + (k >> 1)) % NA), 4);
          bulk_wait();
        }
      }
      __syncwarp();
      if (elect()) {
        flag_set(g_flags + FL_CS + 8 * m + j);
        if (m == 0) flag_add(g_flags + 2 * i * 64 + FL_S0);
        if (m == 0) l2_prefetch((const char*)P.wo + (i * 8 + j) * (D_ * D_ * 2 / 128), D_ * D_ * 2 / 128);
      }
#pragma unroll 1
      for (int k = m; k < 2; k++) flag_wait(k ? g_flags + FL_CS + 8 * m + j : g_flags + 2 * i * 64 + FL_S0, ep * (k ? 16 : 8));
      if (elect()) { mbar_arrive_n(sb + B_CSQ + 8 * m, 8); }
    } else {
      const int ph = step == 1 ? 0 : step - 2, l = ph >> 1;
      mbar_wait(sb + B_LATE, ph & 1);
      if (!(ph & 1)) mbar_wait(sb + B_GO, l);
      if (elect()) {
        if (!(ph & 1)) {
#pragma unroll 1
          for (int gg = 0; gg < 10; gg++)
            bulk_st(g_kv + (size_t)((l * 8 + j) * 2 + 1) * 327680 + gg * 32768 + i * 2048, sb + kv_unit(1) * UNIT + gg * 6144 + 4096, 2048);
          bulk_wait();
          mbar_arrive(sb + B_KVFREE + 8);
        }
        fence_gpu();
        if (ph & 1) {
          flag_add(g_flags + 2 * i * 64 + FL_H + l * 2 + 1); flag_add(g_flags + (2 * i + 1) * 64 + FL_H + l * 2 + 1);
        } else {
          unsigned* fl = g_flags + (2 * i + 2) * 64 + FL_KV + l * 16 + j * 2 + 1;
          flag_add(fl, 2); flag_add(fl + 128, 2);
        }
      }
      __syncwarp();
      if (ph & 1) {
#pragma unroll 1
        for (int k = 0; k < 2; k++) flag_wait(g_flags + (2 * i + k) * 64 + FL_H + l * 2 + 1, ep * 8);
        if (elect()) mbar_arrive_n(sb + B_HL, 2);
      }
    }
  }
}

struct Stats {
  float s0, q0, s1, q1;
  __device__ __forceinline__ void add(float a, float b, float c, float d) {
    s0 += a + b; q0 = fmaf(a, a, fmaf(b, b, q0)); s1 += c + d; q1 = fmaf(c, c, fmaf(d, d, q1));
  }
  __device__ __forceinline__ void quad() {
#pragma unroll
    for (int k = 1; k < 4; k *= 2) {
      s0 += __shfl_xor_sync(~0u, s0, k); q0 += __shfl_xor_sync(~0u, q0, k); s1 += __shfl_xor_sync(~0u, s1, k); q1 += __shfl_xor_sync(~0u, q1, k);
    }
  }
  __device__ __forceinline__ void store(float2* row, int q) {
    quad();
    if (q < 2) row[q * 64] = q ? make_float2(s1, q1) : make_float2(s0, q0);
  }
};
template <bool HEAD, class Wait, class Publish>
__device__ __forceinline__ void attention(uint32_t kd0, uint32_t kd1, uint32_t (&qf)[4][6], int gmin, int dm, int lane, unsigned char* ost,
                                          bool signal, Wait wait, Publish publish) {
  constexpr float C = 0.22360679774997896f * 1.4426950408889634f;
  constexpr float NEG = -1e30f;
  constexpr uint32_t GS = 6144 >> 4;
#pragma unroll 1
  for (int h = 0; h < 4; h++) {
    asm volatile("" : "+r"(dm));
    const bool odd = h & 1;
    const uint32_t kd = h < 2 ? kd0 : kd1;
    if (h == 2) wait();
    float s[160];
    {
      uint32_t z0 = (uint32_t)(dm + 64) >> 8, z1 = (uint32_t)(dm + 65) >> 8;
      const uint32_t k16 = kd + (odd ? 3 * GS : 0) + dlo(0, 6144), k8 = kd + 2 * GS + dlo(0, 6144);
      wg_fence();
      wgmma_rs160_init(s, qf[0][0], qf[0][1], qf[0][2], qf[0][3], desc(k16, dhi(128, 0)));
      wgmma_rs160_init(s + 80, qf[0][0], qf[0][1], qf[0][2], qf[0][3], desc(k16 + 160, dhi(128, 0)));
      wgmma_rs160(s, qf[0][4], qf[0][5], z0, z1, desc(k8, dhi(128, 0)));
      wgmma_rs160(s + 80, qf[0][4], qf[0][5], z0, z1, desc(k8 + 160, dhi(128, 0)));
      wg_commit();
      wg_wait<0>();
      pin(s);
      asm volatile("" : "+r"(qf[0][0]), "+r"(qf[0][1]), "+r"(qf[0][2]), "+r"(qf[0][3]), "+r"(qf[0][4]), "+r"(qf[0][5]), "+r"(z0), "+r"(z1) :: "memory");
    }
#pragma unroll
    for (int k = 0; k < 6; k++) { qf[0][k] = qf[1][k]; qf[1][k] = qf[2][k]; qf[2][k] = qf[3][k]; }
#pragma unroll
    for (int n = 0; n < 8; n++)
#pragma unroll
      for (int e = 0; e < 4; e++) s[4 * n + e] = dm + 8 * (n - (e >> 1)) + (e & 1) > 0 ? (HEAD ? NEG : s[4 * n + e]) : s[128 + 4 * n + e];
    int i0 = __float_as_int(s[0]), i1 = __float_as_int(s[2]), i2 = __float_as_int(s[1]), i3 = __float_as_int(s[3]);
#pragma unroll
    for (int grp = 0; grp < 4; grp++) {
      const int k0 = i0, k1 = i1, k2 = i2, k3 = i3;
#pragma unroll
      for (int n = 8 * grp; n < 8 * grp + 8; n += 2) {
        if (n) { i0 = __vimax3_s32(i0, __float_as_int(s[4 * n]), __float_as_int(s[4 * n + 1])); i1 = __vimax3_s32(i1, __float_as_int(s[4 * n + 2]), __float_as_int(s[4 * n + 3])); }
        i2 = __vimax3_s32(i2, __float_as_int(s[4 * n + 4]), __float_as_int(s[4 * n + 5])); i3 = __vimax3_s32(i3, __float_as_int(s[4 * n + 6]), __float_as_int(s[4 * n + 7]));
      }
      if (HEAD && grp) { const bool out = grp < gmin; i0 = out ? k0 : i0; i1 = out ? k1 : i1; i2 = out ? k2 : i2; i3 = out ? k3 : i3; }
    }
    i0 = max(i0, i2); i1 = max(i1, i3);
    i0 = max(i0, __shfl_xor_sync(~0u, i0, 1)); i1 = max(i1, __shfl_xor_sync(~0u, i1, 1));
    i0 = max(i0, __shfl_xor_sync(~0u, i0, 2)); i1 = max(i1, __shfl_xor_sync(~0u, i1, 2));
    if (__any_sync(~0u, (i0 | i1) < 0)) {
      unsigned u0 = ~0u, u1 = ~0u;
#pragma unroll
      for (int n = 0; n < 32; n++) {
        if (HEAD && n >= 8 && (n >> 3) < gmin) continue;
        u0 = __vimin3_u32(u0, __float_as_uint(s[4 * n]), __float_as_uint(s[4 * n + 1])); u1 = __vimin3_u32(u1, __float_as_uint(s[4 * n + 2]), __float_as_uint(s[4 * n + 3]));
      }
      u0 = min(u0, __shfl_xor_sync(~0u, u0, 1)); u1 = min(u1, __shfl_xor_sync(~0u, u1, 1));
      u0 = min(u0, __shfl_xor_sync(~0u, u0, 2)); u1 = min(u1, __shfl_xor_sync(~0u, u1, 2));
      if (i0 < 0) i0 = u0;
      if (i1 < 0) i1 = u1;
    }
    float m0 = __int_as_float(i0) * -C, m1 = __int_as_float(i1) * -C;
    if (signal && h == 0) asm volatile("bar.arrive 2, 256;" : "+f"(m0), "+f"(m1) :: "memory");
    const uint32_t vd = kd + (odd ? 7 * GS : 5 * GS) + dlo(0, 128);
    float o[12], l0 = 0.f, l1 = 0.f, l2 = 0.f, l3 = 0.f;
#define PINL do { p[3][3] ^= (__float_as_uint(l0 + l1 + l2 + l3) == 0x7fc12345u); } while (0)
    auto expo = [&](int t, uint32_t (&p)[4], float c0, float c1) {
      float e[8];
#pragma unroll
      for (int k = 0; k < 8; k++) e[k] = ex2(fmaf(s[8 * t + k], C, (k & 2) ? c1 : c0));
      l0 += e[0] + e[1]; l1 += e[2] + e[3]; l2 += e[4] + e[5]; l3 += e[6] + e[7];
#pragma unroll
      for (int k = 0; k < 4; k++) p[k] = pack(e[2 * k], e[2 * k + 1]);
    };
    auto pv = [&](const uint32_t (&p)[4], int t) { wgmma_rs24(o, p[0], p[1], p[2], p[3], desc(vd + t * 16, dhi(6144, 0))); };
    {
      uint32_t p[4][4], pn[4][4];
#pragma unroll
      for (int t = 0; t < 4; t++) {
        expo(t, p[t], m0, m1);
#pragma unroll
        for (int k = 0; k < 4; k++) {
          const int x = dm + 8 * (2 * t + (k >> 1) - (k & 1));
          const uint32_t keep = x > 0 ? 0xffffffffu : x == 0 ? 0xffff0000u : 0u;
          pn[t][k] = p[t][k] & ~keep; p[t][k] &= keep;
        }
      }
      PINL;
      wg_fence();
      wgmma_rs24_init(o, p[0][0], p[0][1], p[0][2], p[0][3], desc(vd, dhi(6144, 0)));
      pv(pn[0], 16);
#pragma unroll
      for (int t = 1; t < 4; t++) { pv(p[t], t); pv(pn[t], 16 + t); }
      wg_commit();
    }
#pragma unroll
    for (int grp = 0; grp < 3; grp++) {
      uint32_t p[4][4];
      const bool out = HEAD && grp + 1 < gmin;
#pragma unroll
      for (int t = 0; t < 4; t++) expo(4 + 4 * grp + t, p[t], out ? NEG : m0, out ? NEG : m1);
      PINL;
      wg_fence();
#pragma unroll
      for (int t = 0; t < 4; t++) pv(p[t], 4 + 4 * grp + t);
      wg_commit();
    }
    l0 += l2; l1 += l3;
    l0 += __shfl_xor_sync(~0u, l0, 1); l1 += __shfl_xor_sync(~0u, l1, 1);
    l0 += __shfl_xor_sync(~0u, l0, 2); l1 += __shfl_xor_sync(~0u, l1, 2);
    l0 = __fdividef(1.f, l0); l1 = __fdividef(1.f, l1);
    wg_wait<0>();
    pin(o);
    const bool hi = (lane & 3) >= 2;
    unsigned char* oa = ost + (h >> 1) * 5120 + (odd ? 2048 : 0);
    if (!odd || hi) { stg32(oa, pack(o[0] * l0, o[1] * l0)); stg32(oa + 128, pack(o[2] * l1, o[3] * l1)); }
    stg32(oa + 1024, pack(o[4] * l0, o[5] * l0)); stg32(oa + 1152, pack(o[6] * l1, o[7] * l1));
    if (odd || !hi) { stg32(oa + 2048, pack(o[8] * l0, o[9] * l0)); stg32(oa + 2176, pack(o[10] * l1, o[11] * l1)); }
    if (odd) publish(h);
  }
}

__device__ __forceinline__ float gelu_h(float h) {
  float w = fmaf(h * h, 8.f * 0.7978845608028654f * 0.044715f, 2.f * 0.7978845608028654f);
  return fmaf(h, tanh_(h * w), h);
}

__device__ __forceinline__ void consumer(const Params& P, uint32_t sb, int rank, int i, int j, int warp8) {
  const int wg = warp8 >> 2, warp = warp8 & 3, hb = 2 * i + wg;
  int lane, g, q;
  uint32_t wempty_cl, frag;
  auto section = [&]() {
    asm volatile("mov.u32 %0, %%laneid;" : "=r"(lane));
    g = lane >> 2; q = lane & 3; frag = (warp * 16 + g) * 16 + q * 4;
    wempty_cl = mapa(sb + B_WEMPTY, lane == 0 ? rank : rank ^ 1);
  };
  const uint32_t aslot = sb + SM_A + wg * NA * ASLOT, afull = sb + B_AFULL + wg * NA * 8, aempty = sb + B_AEMPTY + wg * NA * 8;
  const uint32_t staged = sb + B_STAGED + wg * 32, wfull = sb + B_WFULL;
  const uint32_t wd = (sb & 0x3FFFF) >> 4, ad = (aslot & 0x3FFFF) >> 4;
  Ring<NU> w{0, 0};
  Ring<NA> a{0, 0};
  int stg = 0;
  auto rel_w = [&](int u) { if (lane < 2) mbar_arrive_cl(wempty_cl + 8 * u); };
  auto rel_a = [&](int s) { if (lane == 0) mbar_arrive(aempty + 8 * s); };
  auto publish = [&]() { __syncwarp(); if (lane == 0) mbar_arrive(staged + 8 * stg); stg = (stg + 1) & 3; };

  int pa = 0, pw = 0;
  auto ln_gemm = [&](bool swz, auto mma, auto extra) {
    const uint32_t alo = ad + (swz ? dlo(0, 16) : dlo(0, 1024)), astep = swz ? 2 : 128;
    const uint32_t ahi = swz ? dhi(1024, 1) : dhi(128, 0), ahi4 = swz ? dhi(256, 3) : dhi(128, 0);
#pragma unroll 1
    for (int o = 0; o < 4; o++) {
      uint32_t da = 0, db = 0;
      int pa2 = 0;
#pragma unroll
      for (int s = 0; s < 10; s++) {
        if (s % 2 == 0) { mbar_wait(wfull + 8 * w.s, w.ph); db = wd + w.s * (UNIT >> 4); }
        if (s % 5 == 0) { mbar_wait(afull + 8 * a.s, a.ph); da = alo + a.s * (ASLOT >> 4); }
        if (s % 2 == 0 || s == 5) wg_fence();
        mma(s % 5 == 4 ? desc(da + 512, ahi4) : desc(da + (s % 5) * astep, ahi), db, s & 1);
        if (s == 4) { pa2 = a.s; a.adv(); }
        if (s & 1) {
          wg_commit(); wg_wait<1>();
          if (s > 1 || o) rel_w(pw);
          if (s == 1 && o) rel_a(pa);
          if (s == 7) rel_a(pa2);
          pw = w.s; w.adv();
        }
      }
      pa = a.s; a.adv();
      extra(o);
    }
  };
  auto row_factors = [&](int ph, float& rs0, float& nm0, float& rs1, float& nm1) {
    section();
    mbar_wait(sb + B_ST + 8 * wg, ph & 1);
    const float2 f0 = lds64f(sb + SM_LN + (warp8 * 16 + g) * 8), f1 = lds64f(sb + SM_LN + (warp8 * 16 + g + 8) * 8);
    rs0 = f0.x; nm0 = f0.y; rs1 = f1.x; nm1 = f1.y;
  };
  auto late = [&]() { __syncwarp(); if (lane == 0) mbar_arrive(sb + B_LATE); };
  {
    section();
    mbar_wait(afull, 0);
    Stats st{0.f, 0.f, 0.f, 0.f};
#pragma unroll
    for (int t = 0; t < 10; t++) {
      const uint32_t x0 = lds32(aslot + (warp * 16 + g) * 160 + q * 4 + t * 16), x1 = lds32(aslot + (warp * 16 + g + 8) * 160 + q * 4 + t * 16);
      st.add(blo(x0), bhi(x0), blo(x1), bhi(x1));
    }
    st.store(g_st + (hb * 64 + warp * 16 + g) * 8 + j, q);
    rel_a(0); a.adv();
  }
  cluster_wait();

#pragma unroll 1
  for (int ph = 0; ph < NPH; ph++) {
    const int l = ph >> 1;
    section();
    float acc80[40];
    if (!(ph & 1)) {
      uint32_t qf[4][6];
      {
        float acc[96], acr[24];
        if (ph == 0) {
          uint32_t one = 0x3F803F80u + ((uint32_t)lane >> 5), lo = rank ? 0u : one, hi = rank ? one : 0u;
          mbar_wait(wfull + 8 * rank, 0); mbar_wait(wfull + 8 * rank + 8, 0);
          const uint32_t half = wd + (UNIT >> 4), st = wg ? 96 : 384, s0 = rank ? half + st : wd, s1 = rank ? half + (UNIT >> 4) : wd + st;
          float2* dst = (float2*)(g_cs + (i * 8 + j) * 240) + q;
          if (wg == 0) {
            wg_fence();
            wgmma_rs192_init(acc, lo, lo, hi, hi, desc(half + dlo(0, 2048), dhi(1024, 1)));
            wgmma_rs192(acc, one, one, one, one, desc(s0 + dlo(0, 2048), dhi(1024, 1)));
            wgmma_rs192(acc, one, one, one, one, desc(s1 + dlo(0, 2048), dhi(1024, 1)));
            wg_commit(); wg_wait<0>();
            pin(acc);
#pragma unroll
            for (int t = 0; t < 24; t++) if (g == 0 && warp == t / 6) dst[4 * (t / 8 * 10 + t % 8)] = make_float2(acc[4 * t], acc[4 * t + 1]);
          } else {
            wg_fence();
            wgmma_rs48_init(acr, lo, lo, hi, hi, desc(half + dlo(12288, 512), dhi(256, 3)));
            wgmma_rs48(acr, one, one, one, one, desc(s0 + dlo(12288, 512), dhi(256, 3)));
            wgmma_rs48(acr, one, one, one, one, desc(s1 + dlo(12288, 512), dhi(256, 3)));
            wg_commit(); wg_wait<0>();
            pin(acr);
#pragma unroll
            for (int t = 0; t < 6; t++) if (g == 0 && warp == t / 2) dst[4 * (t / 2 * 10 + 8 + t % 2)] = make_float2(acr[4 * t], acr[4 * t + 1]);
          }
          asm volatile("" : "+r"(one), "+r"(lo), "+r"(hi) :: "memory");
          __syncwarp();
          if (lane == 0) mbar_arrive(sb + B_CSP);
        }
        zero(acc); zero(acr);
        ln_gemm(l == 0, [&](uint64_t dA, uint32_t db, int e) {
          wgmma_n192(acc, dA, desc(db + dlo(e * 6144, 2048), dhi(1024, 1)));
          wgmma_n48(acr, dA, desc(db + dlo(12288 + e * 1536, 512), dhi(256, 3)));
        }, [&](int o) {
        });
        float rs0, nm0, rs1, nm1;
        row_factors(ph, rs0, nm0, rs1, nm1);
        if (ph == 0) asm volatile("bar.sync 1, 256;" ::: "memory");
        float2 csv[30];
#pragma unroll
        for (int t = 0; t < 30; t++) csv[t] = lds64f(sb + SM_CSQ + (t * 8 + 2 * q) * 4);
        wg_wait<0>();
        rel_a(pa); rel_w(pw);
        pin(acc); pin(acr);
        if (ph == 0) { a.adv(); a.adv(); a.adv(); }
        auto cvt = [&](int sec, int t, uint32_t& r0, uint32_t& r1) {
          const float* c = t < 8 ? &acc[(sec * 8 + t) * 4] : &acr[(sec * 2 + t - 8) * 4];
          const float2 cs = csv[sec * 10 + t];
          r0 = pack(fmaf(c[0], rs0, nm0 * cs.x), fmaf(c[1], rs0, nm0 * cs.y));
          r1 = pack(fmaf(c[2], rs1, nm1 * cs.x), fmaf(c[3], rs1, nm1 * cs.y));
        };
        uint32_t r[2][10][2];
        unsigned char* gd = g_kv + (size_t)((l * 8 + j) * 2) * 327680 + (128 * i + warp8 * 16 + g) * 16 + q * 4;
#pragma unroll
        for (int p = 0; p < 2; p++) {
#pragma unroll
          for (int t = 0; t < 10; t++) {
            cvt(1 + t / 5, 5 * p + t % 5, r[p][t][0], r[p][t][1]);
            if (p == 0) { stg32(gd + t * 32768, r[p][t][0]); stg32(gd + t * 32768 + 128, r[p][t][1]); }
          }
          if (p == 0) publish();
          mbar_wait(wfull + 8 * (kv_unit(p) + 3), w.ph ^ p);
          const uint32_t dst = sb + kv_unit(p) * UNIT + (256 + warp8 * 16 + g) * 16 + q * 4;
#pragma unroll
          for (int t = 0; t < 10; t++) { sts32(dst + t * 6144, r[p][t][0]); sts32(dst + t * 6144 + 128, r[p][t][1]); }
        }
        fence_async_smem();
        late();
#pragma unroll
        for (int p = 0; p < 2; p++) {
          uint32_t r0, r1;
          cvt(0, 5 * p, qf[2 * p][0], qf[2 * p][1]); cvt(0, 5 * p + 1, qf[2 * p][2], qf[2 * p][3]);
          cvt(0, 5 * p + 3, qf[2 * p + 1][0], qf[2 * p + 1][1]); cvt(0, 5 * p + 4, qf[2 * p + 1][2], qf[2 * p + 1][3]);
          cvt(0, 5 * p + 2, r0, r1);
          qf[2 * p][4] = q < 2 ? r0 : 0u; qf[2 * p][5] = q < 2 ? r1 : 0u;
          qf[2 * p + 1][4] = q < 2 ? 0u : r0; qf[2 * p + 1][5] = q < 2 ? 0u : r1;
        }
        asm volatile("bar.sync 1, 256;" ::: "memory");
      }
      {
        section();
        unsigned char* ost = g_o + (hb * 80 + 10 * j) * 1024 + frag;
        const int gmin = 4 - hb, dm = 2 * q - g - 16 * warp;
        mbar_wait(wfull + 8 * kv_unit(0), w.ph); mbar_wait(wfull + 8 * kv_unit(0) + 8, w.ph);
        w.ph ^= 1;
        if (wg) asm volatile("bar.sync 2, 256;" ::: "memory");
        auto next_pair = [&]() { mbar_wait(wfull + 8 * kv_unit(1), w.ph); mbar_wait(wfull + 8 * kv_unit(1) + 8, w.ph); };
        auto done_pair = [&](int h) { publish(); if (h == 1) { rel_w(4); rel_w(5); rel_w(6); rel_w(7); } };
        const uint32_t kd0 = wd + kv_unit(0) * (UNIT >> 4) + wg * 64, kd1 = wd + kv_unit(1) * (UNIT >> 4) + wg * 64;
        if (i >= 2) attention<false>(kd0, kd1, qf, gmin, dm, lane, ost, wg == 0, next_pair, done_pair);
        else attention<true>(kd0, kd1, qf, gmin, dm, lane, ost, wg == 0, next_pair, done_pair);
        rel_w(0); rel_w(1); rel_w(2); rel_w(3);
      }
      zero(acc80);
    } else {
      float acc[112];
      zero(acc);
      ln_gemm(false, [&](uint64_t dA, uint32_t db, int e) { wgmma_n224(acc, dA, desc(db + dlo(e * 7168, 512), dhi(256, 3))); }, [&](int o) {
      });
      float rs0, nm0, rs1, nm1;
      row_factors(ph, rs0, nm0, rs1, nm1);
      if (ph == 1) asm volatile("bar.sync 1, 256;" ::: "memory");
      unsigned char *dst = g_h + (hb * 108 + HE * j) * 2048 + frag, *dlate = g_h + (hb * 108 + hlate(j) - HE) * 2048 + frag;
      uint32_t cba = sb + SM_CB1 + q * 16;
      wg_wait<0>();
      rel_a(pa); rel_w(pw);
      pin(acc);
      uint32_t hp[56] = {};
#pragma unroll 1
      for (int hf = 0; hf < 2; hf++) {
#pragma unroll
        for (int k = 0; k < 28; k++) hp[k] = hp[k + 28];
#pragma unroll
        for (int p = 0; p < 2; p++) {
          float4 cbv[7];
#pragma unroll
          for (int t = 0; t < 7; t++) cbv[t] = lds128f(cba + (7 * p + t) * 64);
#pragma unroll
          for (int t = 0; t < 7; t++) {
            const int tt = 7 * p + t;
            const float4 cb = cbv[t];
            const float* c = &acc[tt * 4];
            const uint32_t r0 = pack(gelu_h(fmaf(c[0], rs0, fmaf(nm0, cb.x, cb.y))), gelu_h(fmaf(c[1], rs0, fmaf(nm0, cb.z, cb.w))));
            const uint32_t r1 = pack(gelu_h(fmaf(c[2], rs1, fmaf(nm1, cb.x, cb.y))), gelu_h(fmaf(c[3], rs1, fmaf(nm1, cb.z, cb.w))));
            const bool real = tt < 12 || !(hf & j & 1);
            unsigned char* d = (tt < 2 * HE ? dst : dlate) + tt * 1024;
            if (real) { stg32(d, r0); stg32(d + 128, r1); }
            if (tt == 2 * HE - 1 && hf == 0) publish();
            hp[28 + 2 * tt] = real ? r0 : 0u; hp[29 + 2 * tt] = real ? r1 : 0u;
          }
        }
        dst = dlate += 14 * 1024;
        cba += 14 * 64;
#pragma unroll
        for (int k = 0; k < 56; k++) acc[k] = acc[k + 56];
      }
      late();
#pragma unroll
      for (int s = 0; s < 14; s++) {
        if (s % 5 == 0) { mbar_wait(wfull + 8 * (s / 5), w.ph); wg_fence(); }
        const uint64_t db = desc(wd + (s / 5) * (UNIT >> 4) + (s % 5) * 160 + dlo(0, 512), dhi(256, 3));
        if (s == 0) wgmma_rs80_init(acc80, hp[0], hp[1], hp[2], hp[3], db);
        else wgmma_rs80(acc80, hp[4 * s], hp[4 * s + 1], hp[4 * s + 2], hp[4 * s + 3], db);
      }
      wg_commit(); wg_wait<0>();
      pin(acc80);
#pragma unroll
      for (int k = 0; k < 56; k++) asm volatile("" : "+r"(hp[k]) :: "memory");
      rel_w(0); rel_w(1); rel_w(2);
      w.s = 3;
    }
    {
      const bool mlp = ph & 1;
      section();
      float (&acc)[40] = acc80;
      const uint32_t bhi_ = mlp ? dhi(256, 3) : dhi(1280, 3);
      const int nit = mlp ? 19 : 8;
#pragma unroll 1
      for (int it = 0; it < nit; it++) {
        constexpr int NS = 5;
        mbar_wait(afull + 8 * a.s, a.ph); mbar_wait(wfull + 8 * w.s, w.ph);
        const uint32_t da = ad + dlo(0, 1024) + a.s * (ASLOT >> 4), db = wd + w.s * (UNIT >> 4) + (mlp ? dlo(0, 512) : dlo(0, 256));
        wg_fence();
#pragma unroll
        for (int s = 0; s < NS; s++) {
          wgmma_n80(acc, desc(da + s * 128, dhi(128, 0)), desc(db + s * 160, bhi_));
          if (s == 0) {
            wg_commit(); wg_wait<1>();
            if (it) { rel_a(pa); rel_w(pw); }
          }
        }
        wg_commit();
        pa = a.s; pw = w.s; a.adv(); w.adv();
      }
      if (mlp) { w.s = 0; w.ph ^= 1; }
      const bool last = ph == NPH - 1;
      const uint32_t rowm = aslot + a.s * ASLOT + (warp * 16 + g) * 160 + q * 4, core = aslot + a.s * ASLOT + frag;
      float res[40];
      mbar_wait(afull + 8 * a.s, a.ph);
      {
        const uint32_t xs = ph ? core : rowm, ts = ph ? 1024 : 16, rs = ph ? 128 : 1280;
#pragma unroll
        for (int t = 0; t < 10; t++) {
          const uint32_t x0 = lds32(xs + t * ts), x1 = lds32(xs + t * ts + rs);
          const float2 b2 = lds64f(sb + (mlp ? SM_B2 : SM_ZERO) + (t * 8 + 2 * q) * 4);
          res[4 * t] = b2.x + blo(x0); res[4 * t + 1] = b2.y + bhi(x0); res[4 * t + 2] = b2.x + blo(x1); res[4 * t + 3] = b2.y + bhi(x1);
        }
        pin(res);
      }
      asm volatile("bar.sync %0, 128;" :: "r"(3 + wg) : "memory");
      wg_wait<0>();
      rel_a(pa); rel_w(pw);
      pin(acc);
      unsigned char* dst = g_act + ((mlp ? G_X2 : G_X1) + (hb * 80 + 10 * j) * 1024 + frag);
      const uint32_t ds = last ? rowm : core, ts = last ? 16 : 1024, rs = last ? 1280 : 128;
#pragma unroll
      for (int t = 0; t < 10; t++) {
#pragma unroll
        for (int e = 0; e < 4; e++) acc[4 * t + e] += res[4 * t + e];
        const uint32_t r0 = pack(acc[4 * t], acc[4 * t + 1]), r1 = pack(acc[4 * t + 2], acc[4 * t + 3]);
        if (!last) { stg32(dst + t * 1024, r0); stg32(dst + t * 1024 + 128, r1); }
        sts32(ds + t * ts, r0); sts32(ds + t * ts + rs, r1);
      }
      if (!last) {
        Stats st{0.f, 0.f, 0.f, 0.f};
#pragma unroll
        for (int t = 0; t < 10; t++) st.add(acc[4 * t], acc[4 * t + 1], acc[4 * t + 2], acc[4 * t + 3]);
        st.store(g_st + (((ph + 1) * 32 + hb) * 64 + warp * 16 + g) * 8 + j, q);
      }
      if (!last) publish();
      fence_async_smem();
      if (last) publish();
      asm volatile("bar.sync %0, 128;" :: "r"(3 + wg) : "memory");
    }
  }
}

__global__ void __cluster_dims__(2, 1, 1) __launch_bounds__(384, 1)
fused_layers_kernel(const __grid_constant__ Maps maps, const Params P) {
  extern __shared__ unsigned char smem_raw[];
  const uint32_t sb = (s2u(smem_raw) + 1023) & ~1023u;
  const int rank = blockIdx.x & 1, c = blockIdx.x >> 1;
  int pr, j;
  if (c < 4) { pr = 0; j = c; }
  else if (c < 36) { pr = (c - 4) & 7; j = ((c - 4) >> 3) + (pr == 0 ? 4 : 0); }
  else { pr = 1 + (c - 36) % 7; j = 4 + (c - 36) / 7; }
  const int i = 2 * pr + rank;
  const int warp = __shfl_sync(~0u, threadIdx.x >> 5, 0), lane = threadIdx.x & 31;
  if (lane == 0) {
    if (warp < sizeof(Maps) / sizeof(CUtensorMap)) prefetch_map(&maps.x0 + warp);
    const int count = 1 << ((0x314422220000ull >> (4 * warp)) & 7);
#pragma unroll
    for (int k = 0; k < 5; k++) mbar_init(sb + SM_BAR + 40 * warp + 8 * k, count);
    asm volatile("fence.mbarrier_init.release.cluster;" ::: "memory");
  }
  __syncthreads();
  cluster_arrive();
  if (warp >= 8) {
    asm volatile("setmaxnreg.dec.sync.aligned.u32 40;");
    if (warp == 8) { cluster_wait(); producer_w(maps, sb, rank, i, j); }
    else if (warp < 11) producer_a(maps, P, sb, i, j, warp - 9, lane);
    else misc_warp(maps, P, sb, i, j, lane);
    __syncwarp();
    cluster_arrive(); cluster_wait();
  } else {
    asm volatile("setmaxnreg.inc.sync.aligned.u32 232;");
    consumer(P, sb, rank, i, j, warp);
    cluster_arrive(); cluster_wait();
  }
}

typedef CUresult (*EncodeFn)(CUtensorMap*, CUtensorMapDataType, cuuint32_t, void*, const cuuint64_t*, const cuuint64_t*, const cuuint32_t*,
                             const cuuint32_t*, CUtensorMapInterleave, CUtensorMapSwizzle, CUtensorMapL2promotion, CUtensorMapFloatOOBfill);

void encode(EncodeFn enc, CUtensorMap* m, const void* p, int rank, cuuint64_t d0, cuuint64_t d1, cuuint64_t d2, cuuint64_t s1, cuuint64_t s2,
            cuuint32_t b0, cuuint32_t b1, cuuint32_t b2, CUtensorMapSwizzle sw) {
  cuuint64_t gd[3] = {d0, d1, d2}, gs[2] = {s1, s2};
  cuuint32_t bd[3] = {b0, b1, b2}, es[3] = {1, 1, 1};
  enc(m, CU_TENSOR_MAP_DATA_TYPE_BFLOAT16, rank, const_cast<void*>(p), gd, gs, bd, es, CU_TENSOR_MAP_INTERLEAVE_NONE, sw,
      CU_TENSOR_MAP_L2_PROMOTION_L2_128B, CU_TENSOR_MAP_FLOAT_OOB_FILL_NONE);
}

}

extern "C" void kernel_launch(void* const* d_in, const int* in_sizes, int n_in, void* d_out, int out_size) {
  (void)in_sizes; (void)n_in; (void)out_size;
  static EncodeFn enc = nullptr;
  if (!enc) {
    cudaDriverEntryPointQueryResult qr;
    cudaGetDriverEntryPoint("cuTensorMapEncodeTiled", (void**)&enc, cudaEnableDefault, &qr);
    cudaFuncSetAttribute(fused_layers_kernel, cudaFuncAttributeMaxDynamicSharedMemorySize, SMEM_BYTES);
  }
  Params P;
  P.x = (const bf16*)d_in[0]; P.wqkv = (const bf16*)d_in[1]; P.wo = (const bf16*)d_in[2];
  P.w1 = (const bf16*)d_in[4]; P.b1 = (const bf16*)d_in[5]; P.w2 = (const bf16*)d_in[6]; P.b2 = (const bf16*)d_in[7];
  Maps m;
  encode(enc, &m.x0, P.x, 2, D_, S_, 1, D_ * 2, 0, 64, 64, 1, CU_TENSOR_MAP_SWIZZLE_128B);
  encode(enc, &m.x16, P.x, 2, D_, S_, 1, D_ * 2, 0, 16, 64, 1, CU_TENSOR_MAP_SWIZZLE_32B);
  encode(enc, &m.xr, P.x, 2, D_, S_, 1, D_ * 2, 0, 80, 64, 1, CU_TENSOR_MAP_SWIZZLE_NONE);
  encode(enc, &m.q64, P.wqkv, 3, D_, D_, 3, 3 * D_ * 2, D_ * 2, 64, 16, 3, CU_TENSOR_MAP_SWIZZLE_128B);
  encode(enc, &m.q16, P.wqkv, 3, D_, D_, 3, 3 * D_ * 2, D_ * 2, 16, 16, 3, CU_TENSOR_MAP_SWIZZLE_32B);
  encode(enc, &m.wo, P.wo, 3, 16, D_, D_ / 16, D_ * 2, 32, 16, 8, 5, CU_TENSOR_MAP_SWIZZLE_32B);
  encode(enc, &m.out, d_out, 2, D_, S_, 1, D_ * 2, 0, 80, 64, 1, CU_TENSOR_MAP_SWIZZLE_NONE);
  encode(enc, &m.w1i, P.w1, 3, 16, D_, F_ / 16, F_ * 2, 32, 16, 16, 14, CU_TENSOR_MAP_SWIZZLE_32B);
  encode(enc, &m.w2i, P.w2, 3, 16, F_, D_ / 16, D_ * 2, 32, 16, 16, 5, CU_TENSOR_MAP_SWIZZLE_32B);
  fused_layers_kernel<<<128, 384, SMEM_BYTES>>>(m, P);
}
```
